```python
import torch

def _softmax(x, axis=-1):
    return torch.softmax(x, dim=axis)
def _gelu(x):
    return torch.nn.functional.gelu(x, approximate="tanh")
def _silu(x):
    return torch.nn.functional.silu(x)
def _sigmoid(x):
    return torch.sigmoid(x)
def _layernorm(x, axis=-1, eps=1e-5):
    m = x.mean(dim=axis, keepdim=True)
    v = x.var(dim=axis, keepdim=True, unbiased=False)
    return (x - m) / torch.sqrt(v + eps)
def _scatter_add(tgt, idx, src, axis=0):
    return tgt.clone().index_add_(axis, idx, src)
def _segment_sum(src, seg, n):
    out = torch.zeros((n,) + src.shape[1:], dtype=src.dtype)
    return out.index_add_(0, seg, src)
def _pad(x, pw):
    flat = tuple(v for pair in reversed(pw) for v in pair)
    return torch.nn.functional.pad(x, flat)

kernel_name = 'interleave_layers__sliding_block_cached__mixer_channel_mlp__decode'

def setup_inputs():

    _w = (lambda a: (lambda t: t.to(torch.bfloat16) if t.is_floating_point() else t)(torch.as_tensor(a)))
    def _A_setup():
        B, Sq, D = 8, 1, 640
        Hq, Hkv, Sk, Dh = 32, 32, 4096, 128
        assert Hq % Hkv == 0, (Hq, Hkv)
        return {
            "x": _w((lambda *s: torch.randn(*s, dtype=torch.bfloat16) * 0.05)(B, Sq, D)),
            "k_cache": _w((lambda *s: torch.randn(*s, dtype=torch.bfloat16) * 3.2)(B, Hkv, Sk, Dh)),
            "v_cache": _w((lambda *s: torch.randn(*s, dtype=torch.bfloat16) * 0.4)(B, Hkv, Sk, Dh)),
            "wq": _w((lambda *s: torch.randn(*s, dtype=torch.bfloat16) * 3.2)(D, Hq * Dh) * (D ** -0.5)),
            "wo": _w((lambda *s: torch.randn(*s, dtype=torch.bfloat16) * 0.4)(Hq * Dh, D) * ((Hq * Dh) ** -0.5)),
        }
    _A_in = _A_setup()

    def _B_setup():
        B, S, D, F = 8, 1, 640, 1728
        return {
            "x": _w((lambda *s: torch.randn(*s, dtype=torch.bfloat16) * 0.05)(B, S, D)),
            "w1": _w((lambda *s: torch.randn(*s, dtype=torch.bfloat16) * 1.6)(D, F) * (D ** -0.5)),
            "b1": _w((lambda *s: torch.randn(*s, dtype=torch.bfloat16) * 1.6)(F)),
            "w2": _w((lambda *s: torch.randn(*s, dtype=torch.bfloat16) * 0.1)(F, D) * (F ** -0.5)),
            "b2": _w((lambda *s: torch.randn(*s, dtype=torch.bfloat16) * 0.1)(D)),
        }
    _B_in = _B_setup()

    return {
        "A_x": _A_in["x"],
        "A_k_cache": _A_in["k_cache"],
        "A_v_cache": _A_in["v_cache"],
        "A_wq": _A_in["wq"],
        "A_wo": _A_in["wo"],
        "B_x": _B_in["x"],
        "B_w1": _B_in["w1"],
        "B_b1": _B_in["b1"],
        "B_w2": _B_in["w2"],
        "B_b2": _B_in["b2"],
    }

def reference(A_x, A_k_cache, A_v_cache, A_wq, A_wo, B_x, B_w1, B_b1, B_w2, B_b2):
    def _A_ref(x, k_cache, v_cache, wq, wo):
        B, Sq, D = x.shape
        Hq, Dh = 32, 128
        Hkv, Sk = k_cache.shape[1], k_cache.shape[2]
        W = min(4096, max(256, Sk // 4))
        rep = Hq // Hkv
        q = (lambda x, *d: x.permute(*d))((x @ wq).reshape(B, Sq, Hq, Dh), 0, 2, 1, 3)
        k = (lambda x, n, axis: torch.repeat_interleave(x, n, dim=axis))(k_cache[:, :, Sk - W:, :], rep, axis=1)
        v = (lambda x, n, axis: torch.repeat_interleave(x, n, dim=axis))(v_cache[:, :, Sk - W:, :], rep, axis=1)
        scores = torch.einsum("bhqd,bhkd->bhqk", q, k) * (Dh ** -0.5)
        p = _softmax(scores, axis=-1)
        o = torch.einsum("bhqk,bhkd->bhqd", p, v)
        return (lambda x, *d: x.permute(*d))(o, 0, 2, 1, 3).reshape(B, Sq, Hq * Dh) @ wo

    def _B_ref(x, w1, b1, w2, b2):
        y = _layernorm(x, axis=-1)
        h = _gelu(torch.einsum("bsd,df->bsf", y, w1) + b1)
        return torch.einsum("bsf,fd->bsd", h, w2) + b2

    x = A_x
    x = x + _A_ref(_layernorm(x, axis=-1), A_k_cache, A_v_cache, A_wq, A_wo)
    x = x + _B_ref(_layernorm(x, axis=-1), B_w1, B_b1, B_w2, B_b2)
    x = x + _A_ref(_layernorm(x, axis=-1), A_k_cache, A_v_cache, A_wq, A_wo)
    x = x + _B_ref(_layernorm(x, axis=-1), B_w1, B_b1, B_w2, B_b2)
    return x
```

```cpp
#include <cuda_runtime.h>
#include <cuda_bf16.h>
#include <cuda.h>
#include <stdint.h>

namespace {

constexpr int NB = 8, DM = 640, SK = 4096, WIN = 1024, FF = 1728;
constexpr int NCTA = 128, NTHREADS = 512;
constexpr int SLOT = 8192, NSLOT = 27, NWI = 15, NITEM = NWI + NB * 16;
constexpr int TMP_SLOT = 25;
constexpr int ACT_PAIRS = FF / 32;
constexpr int OUT_PAIR = 63;
#define HOLD 7
#define WINDOW 5
#define POLL_DELAY 400
#define XCH_DELAY 0
constexpr int REG_WORK = 160, REG_MISC = 32;

constexpr int OFF_BAR = NSLOT * SLOT;
constexpr int BAR_FULL = 0, BAR_EMPTY = NSLOT, BAR_O = 2 * NSLOT, BAR_H = BAR_O + 2, BAR_Q = BAR_H + 2,
              BAR_P = BAR_Q + 1, BAR_TMP = BAR_P + 1, BAR_Q1 = BAR_TMP + 1, BAR_INIT = BAR_Q1 + 1;
constexpr int OFF_O = OFF_BAR + 512;
constexpr int OFF_ML = OFF_O + 2 * 8 * 144;
constexpr int OFF_H = OFF_ML + 128;
constexpr int OFF_Q = OFF_H + 2 * 560;
constexpr int OFF_Q1 = OFF_Q + 544;
constexpr int OFF_CSQ = OFF_Q1 + 1024;
constexpr int OFF_X = OFF_CSQ + 256;
constexpr int SMEM_BYTES = OFF_X + NB * 640;
static_assert(SMEM_BYTES <= 232448, "smem");
static_assert(BAR_INIT < 64, "barriers");
constexpr uint32_t TX_O = 8 * (128 + 8), TX_H = 2 * (256 + 24), TX_Q = 2 * (256 + 12), TX_P = 2 * 9 * 64 * 4;

constexpr float LN_EPS = 1e-5f;
constexpr float LOG2E = 1.4426950408889634f;
constexpr float SCALE = 0.08838834764831845f;
constexpr uint32_t ONES = 0x3F803F80u;

__device__ uint4 g_acc[32 * 256];
__device__ uint4 g_xch[NCTA * 4 * 128];
__device__ unsigned g_arrive;
#define TS(role, idx) do {} while (0)

__device__ __forceinline__ uint32_t clk32() { uint32_t c; asm volatile("mov.u32 %0, %%clock;" : "=r"(c)); return c; }
__device__ __forceinline__ void mbar_init(uint32_t bar, uint32_t cnt) {
    asm volatile("mbarrier.init.shared::cta.b64 [%0], %1;" ::"r"(bar), "r"(cnt) : "memory");
}
__device__ __forceinline__ void mbar_expect(uint32_t bar, uint32_t bytes) {
    asm volatile("mbarrier.arrive.expect_tx.shared::cta.b64 _, [%0], %1;" ::"r"(bar), "r"(bytes) : "memory");
}
__device__ __forceinline__ void mbar_arrive(uint32_t bar) {
    asm volatile("mbarrier.arrive.shared::cta.b64 _, [%0];" ::"r"(bar) : "memory");
}
__device__ __forceinline__ void mbar_wait(uint32_t bar, uint32_t parity) {
    asm volatile(
        "{\n.reg .pred p;\n.reg .u32 n;\nmov.u32 n, 0;\n"
        "W_%=:\n"
        "mbarrier.try_wait.parity.shared::cta.b64 p, [%0], %1, 2000;\n"
        "@p bra D_%=;\n"
        "add.u32 n, n, 1;\nsetp.lt.u32 p, n, 200000;\n@p bra W_%=;\ntrap;\n"
        "D_%=:\n}\n" ::"r"(bar), "r"(parity) : "memory");
}
__device__ __forceinline__ void mbar_wait_cl(uint32_t bar, uint32_t parity) {
    asm volatile(
        "{\n.reg .pred p;\n.reg .u32 n;\nmov.u32 n, 0;\n"
        "W_%=:\n"
        "mbarrier.try_wait.parity.acquire.cluster.shared::cta.b64 p, [%0], %1, 2000;\n"
        "@p bra D_%=;\n"
        "add.u32 n, n, 1;\nsetp.lt.u32 p, n, 200000;\n@p bra W_%=;\ntrap;\n"
        "D_%=:\n}\n" ::"r"(bar), "r"(parity) : "memory");
}
__device__ __forceinline__ void st_async(uint32_t addr, uint32_t v, uint32_t bar) {
    asm volatile("st.async.shared::cluster.mbarrier::complete_tx::bytes.b32 [%0], %1, [%2];" ::"r"(addr), "r"(v), "r"(bar) : "memory");
}
__device__ __forceinline__ void tma2d(uint32_t dst, const CUtensorMap* tm, int x, int y, uint32_t bar, uint64_t pol) {
    asm volatile("cp.async.bulk.tensor.2d.shared::cluster.global.mbarrier::complete_tx::bytes.L2::cache_hint [%0], [%1, {%3, %4}], [%2], %5;"
                 ::"r"(dst), "l"(tm), "r"(bar), "r"(x), "r"(y), "l"(pol) : "memory");
}
__device__ __forceinline__ void ldsm4(uint32_t& r0, uint32_t& r1, uint32_t& r2, uint32_t& r3, uint32_t a) {
    asm volatile("ldmatrix.sync.aligned.m8n8.x4.shared.b16 {%0,%1,%2,%3}, [%4];" : "=r"(r0), "=r"(r1), "=r"(r2), "=r"(r3) : "r"(a));
}
__device__ __forceinline__ void ldsm4t(uint32_t& r0, uint32_t& r1, uint32_t& r2, uint32_t& r3, uint32_t a) {
    asm volatile("ldmatrix.sync.aligned.m8n8.x4.trans.shared.b16 {%0,%1,%2,%3}, [%4];" : "=r"(r0), "=r"(r1), "=r"(r2), "=r"(r3) : "r"(a));
}
__device__ __forceinline__ void mma(float (&c)[4], uint32_t a0, uint32_t a1, uint32_t a2, uint32_t a3, uint32_t b0, uint32_t b1) {
    asm("mma.sync.aligned.m16n8k16.row.col.f32.bf16.bf16.f32 {%0,%1,%2,%3}, {%4,%5,%6,%7}, {%8,%9}, {%0,%1,%2,%3};"
        : "+f"(c[0]), "+f"(c[1]), "+f"(c[2]), "+f"(c[3]) : "r"(a0), "r"(a1), "r"(a2), "r"(a3), "r"(b0), "r"(b1));
}
__device__ __forceinline__ uint4 lds128(uint32_t a) {
    uint4 v; asm volatile("ld.shared.v4.b32 {%0,%1,%2,%3}, [%4];" : "=r"(v.x), "=r"(v.y), "=r"(v.z), "=r"(v.w) : "r"(a)); return v;
}
__device__ __forceinline__ float4 lds128f(uint32_t a) {
    float4 v; asm volatile("ld.shared.v4.f32 {%0,%1,%2,%3}, [%4];" : "=f"(v.x), "=f"(v.y), "=f"(v.z), "=f"(v.w) : "r"(a)); return v;
}
__device__ __forceinline__ uint2 lds64(uint32_t a) {
    uint2 v; asm volatile("ld.shared.v2.b32 {%0,%1}, [%2];" : "=r"(v.x), "=r"(v.y) : "r"(a)); return v;
}
__device__ __forceinline__ float2 lds64f(uint32_t a) {
    float2 v; asm volatile("ld.shared.v2.f32 {%0,%1}, [%2];" : "=f"(v.x), "=f"(v.y) : "r"(a)); return v;
}
__device__ __forceinline__ float lds_bf16(uint32_t a) {
    uint16_t v; asm volatile("ld.shared.u16 %0, [%1];" : "=h"(v) : "r"(a)); return __uint_as_float((uint32_t)v << 16);
}
__device__ __forceinline__ void sts16(uint32_t a, float v) {
    asm volatile("st.shared.u16 [%0], %1;" ::"r"(a), "h"((uint16_t)(__float_as_uint(v) >> 16)) : "memory");
}
__device__ __forceinline__ void sts32(uint32_t a, uint32_t v) { asm volatile("st.shared.b32 [%0], %1;" ::"r"(a), "r"(v) : "memory"); }
__device__ __forceinline__ uint32_t pack2(float lo, float hi) {
    uint32_t d; asm("cvt.rn.bf16x2.f32 %0, %1, %2;" : "=r"(d) : "f"(hi), "f"(lo)); return d;
}
__device__ __forceinline__ float rbf(float x) { return __uint_as_float(pack2(x, 0.f) << 16); }
__device__ __forceinline__ float ex2(float x) { float y; asm("ex2.approx.ftz.f32 %0, %1;" : "=f"(y) : "f"(x)); return y; }
__device__ __forceinline__ float fsqrt(float x) { float y; asm("sqrt.approx.f32 %0, %1;" : "=f"(y) : "f"(x)); return y; }
__device__ __forceinline__ float fdiv(float a, float b) { float y; asm("div.full.f32 %0, %1, %2;" : "=f"(y) : "f"(a), "f"(b)); return y; }
__device__ __forceinline__ float warp_max(float x) {
    int i = __float_as_int(x), m;
    i ^= (i >> 31) & 0x7fffffff;
    asm volatile("redux.sync.max.s32 %0, %1, 0xffffffff;" : "=r"(m) : "r"(i));
    m ^= (m >> 31) & 0x7fffffff;
    return __int_as_float(m);
}
__device__ __forceinline__ float warp_sum(float x) {
#pragma unroll
    for (int o = 16; o; o >>= 1) x += __shfl_xor_sync(0xffffffffu, x, o);
    return x;
}
__device__ __forceinline__ uint4 ld_relaxed(const uint4* p) {
    uint4 v; asm volatile("ld.relaxed.gpu.global.v4.b32 {%0,%1,%2,%3}, [%4];" : "=r"(v.x), "=r"(v.y), "=r"(v.z), "=r"(v.w) : "l"(p) : "memory");
    return v;
}
__device__ __forceinline__ void row_from_slot(int item, uint32_t& slot, uint32_t& par) {
    uint32_t use = (uint32_t)item / NSLOT;
    slot = item - use * NSLOT; par = use & 1;
}
__device__ __forceinline__ int hop_off(int hop) { return (hop >> 3) * 2048 + (hop & 7) * 8; }

struct Params {
    const __nv_bfloat16* x;
    const __nv_bfloat16* b1;
    const __nv_bfloat16* b2;
    __nv_bfloat16* out;
};

__device__ __forceinline__ void xch_send(uint32_t (&s)[4], uint4* dst, uint32_t tag) {
#pragma unroll
    for (int i = 0; i < 4; i++) s[i] = (s[i] & ~1u) | tag;
    asm volatile("st.relaxed.gpu.global.v4.b32 [%0], {%1,%2,%3,%4};" ::"l"(dst), "r"(s[0]), "r"(s[1]), "r"(s[2]), "r"(s[3]) : "memory");
}

template <bool ROUND>
__device__ __forceinline__ void xch_recv_softmax(const uint32_t (&s)[4], const uint4* src, uint32_t tag,
                                                 uint32_t& P0, uint32_t& P1, float& m, float& l) {
    uint4 v; int n = 0;
    while (true) {
        v = ld_relaxed(src);
        if (((((v.x ^ tag) | (v.y ^ tag)) | ((v.z ^ tag) | (v.w ^ tag))) & 1u) == 0) break;
        if (++n > 2000000) __trap();
    }
    __syncwarp();
    float t[4] = {__uint_as_float(s[0]) + __uint_as_float(v.x), __uint_as_float(s[1]) + __uint_as_float(v.y),
                  __uint_as_float(s[2]) + __uint_as_float(v.z), __uint_as_float(s[3]) + __uint_as_float(v.w)};
#pragma unroll
    for (int i = 0; i < 4; i++) t[i] = ROUND ? rbf(rbf(t[i]) * SCALE) * LOG2E : t[i] * (SCALE * LOG2E);
    m = warp_max(fmaxf(fmaxf(t[0], t[1]), fmaxf(t[2], t[3])));
#pragma unroll
    for (int i = 0; i < 4; i++) t[i] = ex2(t[i] - m);
    P0 = pack2(t[0], t[1]);
    P1 = pack2(t[2], t[3]);
    l = warp_sum((t[0] + t[1]) + (t[2] + t[3]));
}

__device__ __forceinline__ void publish_o(const float (&o)[4][4], float m, float l, int k, uint32_t sb, uint32_t rsb,
                                          int src, int lane) {
    const int g = lane >> 2, j = lane & 3;
    float lo = j == 0 ? o[0][0] : j == 1 ? o[1][0] : j == 2 ? o[2][0] : o[3][0];
    float hi = j == 0 ? o[0][2] : j == 1 ? o[1][2] : j == 2 ? o[2][2] : o[3][2];
    uint32_t wd = pack2(lo, hi);
    uint32_t off = OFF_O + k * (8 * 144) + src * 144 + (8 * j + g) * 4, bar = OFF_BAR + (BAR_O + k) * 8;
    st_async(rsb + off, wd, rsb + bar);
    st_async(sb + off, wd, sb + bar);
    if (lane < 4) {
        uint32_t base = (lane & 2) ? sb : rsb;
        st_async(base + OFF_ML + k * 64 + (lane & 1) * 32 + src * 4, __float_as_uint((lane & 1) ? l : m), base + bar);
    }
}

__device__ __forceinline__ void attention_role(uint32_t sb, uint32_t rsb, int w, int lane) {
    const int c = blockIdx.x, r = c & 1;
    const int j = lane & 3, mi = lane >> 3, i8 = lane & 7;
    const uint32_t bars = sb + OFF_BAR;
    uint32_t koff, voff;
    {
        int row = 16 * w + ((mi & 1) ? 8 + ((i8 + 4) & 7) : i8);
        koff = sb + row * 128 + (((mi >> 1) ^ (row & 7)) << 4);
        int gi = (i8 >> 1) + 4 * (mi >> 1);
        row = 16 * w + ((i8 & 1) ? 8 + ((gi + 4) & 7) : gi);
        voff = sb + row * 128 + (((mi & 1) ^ (row & 7)) << 4);
    }
    uint4* const xout = g_xch + (c ^ 2) * 512 + w * 32 + lane;
    const uint4* const xin = g_xch + c * 512 + w * 32 + lane;
    uint32_t hold[HOLD * 16];
    uint32_t s1[4], s2[4];
#pragma unroll
    for (int i = 0; i < HOLD * 16; i++) hold[i] = 0;
#pragma unroll
    for (int i = 0; i < 4; i++) s1[i] = s2[i] = 0;

    mbar_wait(bars + BAR_Q1 * 8, 0);

#pragma unroll 1
    for (int s = -1; s < NB; ++s) {
        const int n = s + 1;
        uint32_t qf[8];
        if (n < NB) {
            uint4 qa = lds128(sb + OFF_Q1 + n * 128 + j * 32), qb = lds128(sb + OFF_Q1 + n * 128 + j * 32 + 16);
            qf[0] = qa.x; qf[1] = qa.y; qf[2] = qa.z; qf[3] = qa.w; qf[4] = qb.x; qf[5] = qb.y; qf[6] = qb.z; qf[7] = qb.w;
            uint32_t sl, par;
            row_from_slot(NWI + 16 * n, sl, par);
#pragma unroll
            for (int ch = 0; ch < 8; ch++) {
                mbar_wait(bars + sl * 8, par);
                const uint32_t base = koff + sl * SLOT;
                float acc[4] = {0.f, 0.f, 0.f, 0.f};
#pragma unroll
                for (int ks = 0; ks < 4; ks++) {
                    uint32_t a0, a1, a2, a3;
                    ldsm4(a0, a1, a2, a3, base ^ (ks << 5));
                    mma(acc, a0, a1, a2, a3, qf[2 * ks], qf[2 * ks + 1]);
                }
                if (j == (ch >> 1)) { s1[(ch & 1) * 2] = __float_as_uint(acc[0]); s1[(ch & 1) * 2 + 1] = __float_as_uint(acc[2]); }
                if (++sl == NSLOT) { sl = 0; par ^= 1; }
            }
            if (n == 0) mbar_wait(bars + BAR_INIT * 8, 0);
            xch_send(s1, xout + (n & 1) * 128, ((n >> 1) & 1) ^ 1);
            TS(0, n * 16 + 0);
        }
        if (s >= 0) {
            mbar_wait_cl(bars + BAR_Q * 8, s & 1);
            TS(0, s * 16 + 4);
            {
                float4 pq = lds128f(sb + OFF_Q + lane * 16);
                float4 st = lds128f(sb + OFF_Q + 512);
                float2 su = lds64f(sb + OFF_Q + 528);
                float2 cs = lds64f(sb + OFF_CSQ + lane * 8);
                if (w == 0 && lane == 0) mbar_expect(bars + BAR_Q * 8, TX_Q);
                float mean = (su.x + su.y) * (1.f / DM);
                float var = fmaxf(((st.x + st.y) + (st.z + st.w)) * (1.f / DM) - mean * mean, 0.f);
                float rs = rsqrtf(var + LN_EPS);
                uint32_t pk = pack2((pq.x + pq.y - mean * cs.x) * rs, (pq.z + pq.w - mean * cs.y) * rs);
#pragma unroll
                for (int i = 0; i < 8; i++) qf[i] = __shfl_sync(0xffffffffu, pk, 4 * i + j);
            }
            uint32_t sl, par;
            row_from_slot(NWI + 16 * s + HOLD, sl, par);
#pragma unroll
            for (int ch = 0; ch < 8; ch++) {
                float acc[4] = {0.f, 0.f, 0.f, 0.f};
                if (ch < HOLD) {
#pragma unroll
                    for (int ks = 0; ks < 4; ks++) {
                        const int o = (ch < HOLD ? ch : 0) * 16 + ks * 4;
                        mma(acc, hold[o], hold[o + 1], hold[o + 2], hold[o + 3], qf[2 * ks], qf[2 * ks + 1]);
                    }
                } else {
                    const uint32_t base = koff + sl * SLOT;
#pragma unroll
                    for (int ks = 0; ks < 4; ks++) {
                        uint32_t a0, a1, a2, a3;
                        ldsm4(a0, a1, a2, a3, base ^ (ks << 5));
                        mma(acc, a0, a1, a2, a3, qf[2 * ks], qf[2 * ks + 1]);
                    }
                    __syncwarp();
                    if (lane == 0) mbar_arrive(bars + (BAR_EMPTY + sl) * 8);
                    if (++sl == NSLOT) sl = 0;
                }
                if (j == (ch >> 1)) { s2[(ch & 1) * 2] = __float_as_uint(acc[0]); s2[(ch & 1) * 2 + 1] = __float_as_uint(acc[2]); }
            }
            xch_send(s2, xout + (2 + (s & 1)) * 128, ((s >> 1) & 1) ^ 1);
            TS(0, s * 16 + 5);
#pragma unroll
            for (int u = 0; u < HOLD; u++) {
                const uint32_t base = voff + sl * SLOT;
#pragma unroll
                for (int mt = 0; mt < 4; mt++) {
                    const int o = u * 16 + mt * 4;
                    ldsm4t(hold[o], hold[o + 1], hold[o + 2], hold[o + 3], base ^ (mt << 5));
                }
                __syncwarp();
                if (lane == 0) mbar_arrive(bars + (BAR_EMPTY + sl) * 8);
                if (++sl == NSLOT) sl = 0;
            }
            TS(0, s * 16 + 6);
        }
        if (n < NB) {
            uint32_t P0, P1; float m, l;
            xch_recv_softmax<true>(s1, xin + (n & 1) * 128, ((n >> 1) & 1) ^ 1, P0, P1, m, l);
            TS(0, n * 16 + 1);
            float o[4][4];
#pragma unroll
            for (int mt = 0; mt < 4; mt++) o[mt][0] = o[mt][1] = o[mt][2] = o[mt][3] = 0.f;
            uint32_t sl, par;
            row_from_slot(NWI + 16 * n + 8, sl, par);
#pragma unroll
            for (int u = 0; u < 8; u++) {
                uint32_t b0 = __shfl_sync(0xffffffffu, (u & 1) ? P1 : P0, 4 * j + (u >> 1));
                uint32_t b1 = __shfl_sync(0xffffffffu, (u & 1) ? P1 : P0, 4 * j + 16 + (u >> 1));
                mbar_wait(bars + sl * 8, par);
                const uint32_t base = voff + sl * SLOT;
#pragma unroll
                for (int mt = 0; mt < 4; mt++) {
                    uint32_t a0, a1, a2, a3;
                    ldsm4t(a0, a1, a2, a3, base ^ (mt << 5));
                    mma(o[mt], a0, a1, a2, a3, b0, b1);
                }
                if (++sl == NSLOT) { sl = 0; par ^= 1; }
            }
            publish_o(o, m, l, 0, sb, rsb, 4 * r + w, lane);
            TS(0, n * 16 + 2);
        }
        if (s >= 0) {
            uint32_t P0, P1; float m, l;
            xch_recv_softmax<false>(s2, xin + (2 + (s & 1)) * 128, ((s >> 1) & 1) ^ 1, P0, P1, m, l);
            TS(0, s * 16 + 7);
            float o[4][4];
#pragma unroll
            for (int mt = 0; mt < 4; mt++) o[mt][0] = o[mt][1] = o[mt][2] = o[mt][3] = 0.f;
            uint32_t sl, par;
            row_from_slot(NWI + 16 * s + 8 + HOLD, sl, par);
#pragma unroll
            for (int u = 0; u < 8; u++) {
                uint32_t b0 = __shfl_sync(0xffffffffu, (u & 1) ? P1 : P0, 4 * j + (u >> 1));
                uint32_t b1 = __shfl_sync(0xffffffffu, (u & 1) ? P1 : P0, 4 * j + 16 + (u >> 1));
                if (u < HOLD) {
#pragma unroll
                    for (int mt = 0; mt < 4; mt++) {
                        const int q = (u < HOLD ? u : 0) * 16 + mt * 4;
                        mma(o[mt], hold[q], hold[q + 1], hold[q + 2], hold[q + 3], b0, b1);
                    }
                } else {
                    const uint32_t base = voff + sl * SLOT;
#pragma unroll
                    for (int mt = 0; mt < 4; mt++) {
                        uint32_t a0, a1, a2, a3;
                        ldsm4t(a0, a1, a2, a3, base ^ (mt << 5));
                        mma(o[mt], a0, a1, a2, a3, b0, b1);
                    }
                    __syncwarp();
                    if (lane == 0) mbar_arrive(bars + (BAR_EMPTY + sl) * 8);
                    if (++sl == NSLOT) sl = 0;
                }
            }
            publish_o(o, m, l, 1, sb, rsb, 4 * r + w, lane);
            TS(0, s * 16 + 8);
        }
        if (n < NB) {
            uint32_t sl, par;
            row_from_slot(NWI + 16 * n, sl, par);
#pragma unroll
            for (int ch = 0; ch < HOLD; ch++) {
                const uint32_t base = koff + sl * SLOT;
#pragma unroll
                for (int ks = 0; ks < 4; ks++) {
                    const int o = ch * 16 + ks * 4;
                    ldsm4(hold[o], hold[o + 1], hold[o + 2], hold[o + 3], base ^ (ks << 5));
                }
                __syncwarp();
                if (lane == 0) mbar_arrive(bars + (BAR_EMPTY + sl) * 8);
                if (++sl == NSLOT) sl = 0;
            }
            TS(0, n * 16 + 3);
        }
    }
}

__device__ __forceinline__ void chain_bar() { asm volatile("bar.sync 1, 256;" ::: "memory"); }

__device__ __forceinline__ void red_out(uint4* p, const float (&v)[3]) {
    asm volatile("red.relaxed.gpu.global.add.v4.f32 [%0], {%1,%2,%3,%4};" ::"l"(p), "f"(v[0]), "f"(v[1]), "f"(v[2]), "f"(1.0f) : "memory");
}

template <bool BIAS>
__device__ __forceinline__ void poll_residual(const uint4* p, uint32_t count_bits, uint32_t xa, int j, uint32_t t0, uint32_t delay,
                                              const float (&bias)[3], float (&x)[3]) {
    if (j < 2) {
        x[0] = lds_bf16(xa); x[1] = lds_bf16(xa + 16); x[2] = j == 0 ? lds_bf16(xa + 32) : 0.f;
        while (clk32() - t0 < delay) {}
        uint4 v; int n = 0;
        while (true) {
            v = ld_relaxed(p);
            if (v.w == count_bits) break;
            if (++n > 2000000) __trap();
        }
        float y[3] = {rbf(__uint_as_float(v.x)), rbf(__uint_as_float(v.y)), rbf(__uint_as_float(v.z))};
#pragma unroll
        for (int i = 0; i < 3; i++) x[i] = rbf(x[i] + (BIAS ? rbf(y[i] + bias[i]) : y[i]));
    }
}

__device__ __forceinline__ void stage_wo(const uint32_t (&WO)[40], int k, uint32_t par, uint4* dst, uint32_t sb, int w, int lane) {
    const int g = lane >> 2, j = lane & 3;
    mbar_wait_cl(sb + OFF_BAR + (BAR_O + k) * 8, par);
    const uint32_t ob = sb + OFF_O + k * (8 * 144) + g * 144 + j * 32, ml = sb + OFF_ML + k * 64;
    uint4 B0 = lds128(ob), B1 = lds128(ob + 16);
    float4 ma = lds128f(ml), mb = lds128f(ml + 16);
    float2 mo = lds64f(ml + 8 * j), lo = lds64f(ml + 32 + 8 * j);
    if (w == 0 && lane == 0) mbar_expect(sb + OFF_BAR + (BAR_O + k) * 8, TX_O);
    const uint32_t B[8] = {B0.x, B0.y, B0.z, B0.w, B1.x, B1.y, B1.z, B1.w};
    float t0[4] = {0.f, 0.f, 0.f, 0.f}, t1[4] = {0.f, 0.f, 0.f, 0.f}, t2[4] = {0.f, 0.f, 0.f, 0.f}, t3[4] = {0.f, 0.f, 0.f, 0.f};
#pragma unroll
    for (int s = 0; s < 4; s++) {
        mma(t0, WO[4 * s], WO[4 * s + 1], WO[4 * s + 2], WO[4 * s + 3], B[2 * s], B[2 * s + 1]);
        mma(t1, WO[16 + 4 * s], WO[16 + 4 * s + 1], WO[16 + 4 * s + 2], WO[16 + 4 * s + 3], B[2 * s], B[2 * s + 1]);
        mma((s & 1) ? t3 : t2, WO[32 + 2 * (s & 2)], WO[33 + 2 * (s & 2)], WO[34 + 2 * (s & 2)], WO[35 + 2 * (s & 2)], B[2 * s], B[2 * s + 1]);
    }
    float M = fmaxf(fmaxf(fmaxf(ma.x, ma.y), fmaxf(ma.z, ma.w)), fmaxf(fmaxf(mb.x, mb.y), fmaxf(mb.z, mb.w)));
    float e0 = ex2(mo.x - M), e1 = ex2(mo.y - M);
    float L = e0 * lo.x + e1 * lo.y;
    L += __shfl_xor_sync(0xffffffffu, L, 1);
    L += __shfl_xor_sync(0xffffffffu, L, 2);
    float inv = __fdividef(1.f, L);
    e0 *= inv; e1 *= inv;
    float v[6] = {e0 * t0[0] + e1 * t0[1], e0 * t0[2] + e1 * t0[3], e0 * t1[0] + e1 * t1[1],
                  e0 * t1[2] + e1 * t1[3], e0 * (t2[0] + t3[2]) + e1 * (t2[1] + t3[3]), 0.f};
    float u[3];
    const bool odd = j & 1;
#pragma unroll
    for (int i = 0; i < 3; i++) u[i] = (odd ? v[3 + i] : v[i]) + __shfl_xor_sync(0xffffffffu, odd ? v[i] : v[3 + i], 1);
#pragma unroll
    for (int i = 0; i < 3; i++) u[i] += __shfl_xor_sync(0xffffffffu, u[i], 2);
    if (j < 2) red_out(dst, u);
}

__device__ __forceinline__ void stage_mlp(const uint32_t (&W1)[20], const uint32_t (&W2)[20], float cs1, float b1v, int k, uint32_t par,
                                          uint32_t xrow, uint4* dst, uint32_t sb, uint32_t jsb, int r, int w, int lane) {
    const int g = lane >> 2, j = lane & 3, ht = w & 3, kh = w >> 2;
    const uint32_t xb = xrow + (kh * 160 + (g & 1) * 80) * 2;
    uint4 B0 = lds128(xb + j * 16), B1 = lds128(xb + 64 + j * 16);
    uint2 B2 = lds64(xb + 128 + j * 8);
    const uint32_t hb = OFF_H + k * 560, bar = OFF_BAR + (BAR_H + k) * 8;
    float a[4] = {0.f, 0.f, 0.f, 0.f}, b[4] = {0.f, 0.f, 0.f, 0.f};
    mma(a, W1[0], W1[1], W1[2], W1[3], B0.x, B0.y);
    mma(b, W1[4], W1[5], W1[6], W1[7], B0.z, B0.w);
    mma(a, W1[8], W1[9], W1[10], W1[11], B1.x, B1.y);
    mma(b, W1[12], W1[13], W1[14], W1[15], B1.z, B1.w);
    mma(a, W1[16], W1[17], W1[18], W1[19], B2.x, B2.y);
    if (ht == 0) {
        float sa[4] = {0.f, 0.f, 0.f, 0.f}, sc[4] = {0.f, 0.f, 0.f, 0.f};
        mma(sa, B0.x, ONES, B0.y, ONES, B0.x, B0.y);
        mma(sc, B0.z, ONES, B0.w, ONES, B0.z, B0.w);
        mma(sa, B1.x, ONES, B1.y, ONES, B1.x, B1.y);
        mma(sc, B1.z, ONES, B1.w, ONES, B1.z, B1.w);
        mma(sa, B2.x, ONES, B2.y, ONES, B2.x, B2.y);
        float sv = g == 0 ? sa[0] + sc[0] : g == 1 ? sa[1] + sc[1] : (sa[2] + sc[2]) + (sa[3] + sc[3]);
        if (g < 3 && j < 2) st_async(jsb + hb + (32 + g) * 16 + (2 * r + kh) * 4, __float_as_uint(sv), jsb + bar);
    }
    if (j < 2) st_async(jsb + hb + (8 * ht + g) * 16 + (2 * r + kh) * 4, __float_as_uint((a[0] + b[0]) + (a[3] + b[3])), jsb + bar);
    mbar_wait_cl(sb + bar, par);
    float4 hp = lds128f(sb + hb + lane * 16), q0 = lds128f(sb + hb + 512), q1 = lds128f(sb + hb + 528), su = lds128f(sb + hb + 544);
    if (w == 0 && lane == 0) mbar_expect(sb + bar, TX_H);
    float mean = ((su.x + su.y) + (su.z + su.w)) * (1.f / DM);
    float var = fmaxf((((q0.x + q0.y) + (q0.z + q0.w)) + ((q1.x + q1.y) + (q1.z + q1.w))) * (1.f / DM) - mean * mean, 0.f);
    float rs = rsqrtf(var + LN_EPS * (var + LN_EPS));
    float pre = rbf(rbf((((hp.x + hp.y) + (hp.z + hp.w)) - mean * cs1) * rs) + b1v);
    float u2 = pre * fmaf(pre * pre, -2.f * LOG2E * 0.7978845608028654f * 0.044715f, -2.f * LOG2E * 0.7978845608028654f);
    float hv = __fdividef(pre, 1.f + ex2(u2));
    const int f0 = 16 * (g & 1) + 2 * j;
    float h0 = __shfl_sync(0xffffffffu, hv, f0), h1 = __shfl_sync(0xffffffffu, hv, f0 + 1);
    float h2 = __shfl_sync(0xffffffffu, hv, f0 + 8), h3 = __shfl_sync(0xffffffffu, hv, f0 + 9);
    const uint32_t b0 = pack2(h0, h1), b1 = pack2(h2, h3);
    float v[5];
#pragma unroll
    for (int e = 0; e < 5; e++) {
        float t[4] = {0.f, 0.f, 0.f, 0.f};
        mma(t, W2[4 * e], W2[4 * e + 1], W2[4 * e + 2], W2[4 * e + 3], b0, b1);
        v[e] = t[0] + t[3];
    }
    const bool odd = j & 1;
    float u[3] = {odd ? v[3] : v[0], odd ? v[4] : v[1], odd ? 0.f : v[2]};
    if (j < 2) red_out(dst, u);
}

__device__ __forceinline__ void chain_role(const Params& P, uint32_t sb, uint32_t rsb, int w, int lane) {
    const int c = blockIdx.x, r = c & 1, p = c >> 1;
    const int g = lane >> 2, j = lane & 3, mi = lane >> 3, ri = lane & 7;
    const uint32_t bars = sb + OFF_BAR;
    const uint32_t jsb = (j & 1) ? rsb : sb;
    const bool active = p < ACT_PAIRS;
    uint32_t WQ[40], WO[40], W1[20], W2[20];

    {
        const uint32_t* xr = reinterpret_cast<const uint32_t*>(P.x + w * DM);
        uint32_t xw[10];
#pragma unroll
        for (int i = 0; i < 10; i++) xw[i] = __ldg(xr + lane + 32 * i);
        float sum = 0.f;
#pragma unroll
        for (int i = 0; i < 10; i++) sum += __uint_as_float(xw[i] << 16) + __uint_as_float(xw[i] & 0xffff0000u);
        const float mean = warp_sum(sum) * (1.f / DM);
        float sq = 0.f;
#pragma unroll
        for (int i = 0; i < 10; i++) {
            float d0 = __uint_as_float(xw[i] << 16) - mean, d1 = __uint_as_float(xw[i] & 0xffff0000u) - mean;
            sq += d0 * d0 + d1 * d1;
        }
        const float mb = rbf(mean), den = rbf(fsqrt(rbf(rbf(warp_sum(sq) * (1.f / DM)) + LN_EPS)));
#pragma unroll
        for (int i = 0; i < 5; i++) {
            uint32_t v = r ? xw[5 + i] : xw[i];
            float d0 = rbf(__uint_as_float(v << 16) - mb), d1 = rbf(__uint_as_float(v & 0xffff0000u) - mb);
            sts32(sb + OFF_X + w * 640 + (lane + 32 * i) * 4, v);
            sts32(sb + TMP_SLOT * SLOT + w * 640 + (lane + 32 * i) * 4, pack2(fdiv(d0, den), fdiv(d1, den)));
        }
    }
#pragma unroll
    for (int i = 0; i < 5; i++) mbar_wait(bars + i * 8, 0);
#pragma unroll
    for (int t = 0; t < 10; t++) {
        int k = (mi & 1) * 160 + 32 * (t >> 1) + 8 * (ri >> 1) + 2 * (2 * (t & 1) + (mi >> 1)) + (ri & 1);
        ldsm4t(WQ[4 * t], WQ[4 * t + 1], WQ[4 * t + 2], WQ[4 * t + 3], sb + k * 128 + ((w ^ (k & 7)) << 4));
    }
    chain_bar();
    if (w < 4 && lane < 5) mbar_arrive(bars + (BAR_EMPTY + lane) * 8);
    {
        const uint32_t px = (TMP_SLOT + 1) * SLOT, pb = OFF_BAR + BAR_P * 8;
#pragma unroll 1
        for (int rd = 0; rd < 3; rd++) {
            const uint32_t xb = sb + TMP_SLOT * SLOT + (4 * (rd & 1) + (g >> 1)) * 640 + ((g & 1) * 160 + 8 * j) * 2;
            float a[4] = {0.f, 0.f, 0.f, 0.f};
#pragma unroll
            for (int blk = 0; blk < 5; blk++) {
                uint4 B = lds128(xb + blk * 64);
                if (rd == 2) B = make_uint4(ONES, ONES, ONES, ONES);
                mma(a, WQ[8 * blk], WQ[8 * blk + 1], WQ[8 * blk + 2], WQ[8 * blk + 3], B.x, B.y);
                mma(a, WQ[8 * blk + 4], WQ[8 * blk + 5], WQ[8 * blk + 6], WQ[8 * blk + 7], B.z, B.w);
            }
            if (rd < 2 || j == 0) {
                uint32_t off = px + ((4 * rd + j) * 64 + 8 * w + g) * 8 + r * 4;
                st_async(sb + off, __float_as_uint(a[0] + a[3]), sb + pb);
                st_async(rsb + off, __float_as_uint(a[0] + a[3]), rsb + pb);
            }
        }
        mbar_wait_cl(sb + pb, 0);
        float4 v = lds128f(sb + px + w * 512 + lane * 16);
        sts32(sb + OFF_Q1 + w * 128 + ((lane & 3) * 8 + (lane >> 2)) * 4, pack2(v.x + v.y, v.z + v.w));
        if (lane < 8) {
            float2 cs = lds64f(sb + px + 8 * 512 + (8 * w + lane) * 8);
            sts32(sb + OFF_CSQ + (8 * w + lane) * 4, __float_as_uint(cs.x + cs.y));
        }
        asm volatile("fence.proxy.async.shared::cta;" ::: "memory");
        __syncwarp();
        if (lane == 0) { mbar_arrive(bars + BAR_Q1 * 8); mbar_arrive(bars + BAR_TMP * 8); }
    }
#pragma unroll
    for (int i = 5; i < 10; i++) mbar_wait(bars + i * 8, 0);
#pragma unroll
    for (int t = 0; t < 10; t++) {
        int cc = 5 * w + (t < 8 ? 2 * (t >> 2) + (mi & 1) : 4);
        int k = 16 * (ri >> 1) + 8 * (ri & 1) + (t < 8 ? 2 * (t & 3) : 4 * (t - 8) + 2 * (mi & 1)) + (mi >> 1);
        ldsm4t(WO[4 * t], WO[4 * t + 1], WO[4 * t + 2], WO[4 * t + 3],
               sb + (5 + (cc >> 3)) * SLOT + k * 128 + (((cc & 7) ^ (k & 7)) << 4));
    }
#pragma unroll
    for (int i = 10; i < 15; i++) mbar_wait(bars + i * 8, 0);
#pragma unroll
    for (int t = 0; t < 5; t++) {
        int kb = (w >> 2) * 160 + (mi & 1) * 80;
        int k = t < 4 ? kb + 32 * (t >> 1) + 8 * (ri >> 1) + 2 * (2 * (t & 1) + (mi >> 1)) + (ri & 1)
                      : kb + 64 + 4 * (ri >> 1) + 2 * (mi >> 1) + (ri & 1);
        ldsm4t(W1[4 * t], W1[4 * t + 1], W1[4 * t + 2], W1[4 * t + 3], sb + (10 + (k >> 6)) * SLOT + (k & 63) * 64 + (w & 3) * 16);
        int cc = 5 * w + t, k2 = 8 * ((mi & 1) * 2 + (mi >> 1)) + ri;
        ldsm4t(W2[4 * t], W2[4 * t + 1], W2[4 * t + 2], W2[4 * t + 3],
               sb + (10 + (cc >> 3)) * SLOT + 4096 + k2 * 128 + (((cc & 7) ^ (k2 & 7)) << 4));
    }
    chain_bar();
    if (w < 4 && lane < 10) mbar_arrive(bars + (BAR_EMPTY + 5 + lane) * 8);
    float cs1 = 0.f, b1v = 0.f, b2v[3];
    if (active) {
        float a[4] = {0.f, 0.f, 0.f, 0.f};
#pragma unroll
        for (int t = 0; t < 5; t++) mma(a, W1[4 * t], W1[4 * t + 1], W1[4 * t + 2], W1[4 * t + 3], ONES, ONES);
        const uint32_t hb = OFF_H + 560, bar = OFF_BAR + (BAR_H + 1) * 8;
        if (j < 2) st_async(jsb + hb + (8 * (w & 3) + g) * 16 + (2 * r + (w >> 2)) * 4, __float_as_uint(a[0] + a[3]), jsb + bar);
        b1v = __bfloat162float(P.b1[32 * p + lane]);
        mbar_wait_cl(sb + bar, 0);
        float4 hp = lds128f(sb + hb + lane * 16);
        if (w == 0 && lane == 0) mbar_expect(sb + bar, TX_H);
        cs1 = (hp.x + hp.y) + (hp.z + hp.w);
    }
    const int col = 40 * w + 24 * (j & 1) + g;
#pragma unroll
    for (int i = 0; i < 3; i++) b2v[i] = (j & 1) && i == 2 ? 0.f : __bfloat162float(P.b2[320 * r + col + 8 * i]);
    uint4* const acc = g_acc + (r * 16 + 2 * w + (g >> 2)) * 64 + ((2 * g + j) & 7);
    const uint32_t xcol = sb + OFF_X + col * 2;
    const uint32_t CNT1 = __float_as_uint(64.f), CNT2 = __float_as_uint((float)ACT_PAIRS);

#pragma unroll 1
    for (int s = 0; s < NB + 2; ++s) {
        float x[3];
        uint32_t t0 = 0;
        if (s < NB) {
            stage_wo(WO, 0, s & 1, acc + hop_off(4 * s), sb, w, lane);
            t0 = clk32();
            TS(1, s * 16 + 0);
            poll_residual<false>(acc + hop_off(4 * s), CNT1, xcol + s * 640, j, t0, POLL_DELAY, b2v, x);
            if (j < 2) { sts16(xcol + s * 640, x[0]); sts16(xcol + s * 640 + 16, x[1]); if (j == 0) sts16(xcol + s * 640 + 32, x[2]); }
            TS(1, s * 16 + 1);
            if (active) {
                chain_bar();
                stage_mlp(W1, W2, cs1, b1v, 0, s & 1, sb + OFF_X + s * 640, acc + hop_off(4 * s + 1), sb, jsb, r, w, lane);
            }
            t0 = clk32();
            TS(1, s * 16 + 2);
        }
        if (s >= 1 && s <= NB) {
            stage_wo(WO, 1, (s - 1) & 1, acc + hop_off(4 * s - 2), sb, w, lane);
            if (s == NB) t0 = clk32();
            TS(1, (s - 1) * 16 + 5);
        }
        if (s < NB) {
            poll_residual<true>(acc + hop_off(4 * s + 1), CNT2, xcol + s * 640, j, t0, POLL_DELAY, b2v, x);
            if (j < 2) { sts16(xcol + s * 640, x[0]); sts16(xcol + s * 640 + 16, x[1]); if (j == 0) sts16(xcol + s * 640 + 32, x[2]); }
            TS(1, s * 16 + 3);
            chain_bar();
            const uint32_t xb = sb + OFF_X + s * 640 + ((g & 1) * 160 + 8 * j) * 2, bar = OFF_BAR + BAR_Q * 8;
            float a[4] = {0.f, 0.f, 0.f, 0.f}, b[4] = {0.f, 0.f, 0.f, 0.f};
            if (w == 0) {
                float sa[4] = {0.f, 0.f, 0.f, 0.f}, sc[4] = {0.f, 0.f, 0.f, 0.f};
#pragma unroll
                for (int blk = 0; blk < 5; blk++) {
                    uint4 B = lds128(xb + blk * 64);
                    mma(a, WQ[8 * blk], WQ[8 * blk + 1], WQ[8 * blk + 2], WQ[8 * blk + 3], B.x, B.y);
                    mma(b, WQ[8 * blk + 4], WQ[8 * blk + 5], WQ[8 * blk + 6], WQ[8 * blk + 7], B.z, B.w);
                    mma(sa, B.x, ONES, B.y, ONES, B.x, B.y);
                    mma(sc, B.z, ONES, B.w, ONES, B.z, B.w);
                }
                float sv = g == 0 ? sa[0] + sc[0] : g == 1 ? sa[1] + sc[1] : (sa[2] + sc[2]) + (sa[3] + sc[3]);
                if (g < 3 && j < 2) st_async(jsb + OFF_Q + 512 + g * 8 + r * 4, __float_as_uint(sv), jsb + bar);
            } else {
#pragma unroll
                for (int blk = 0; blk < 5; blk++) {
                    uint4 B = lds128(xb + blk * 64);
                    mma(a, WQ[8 * blk], WQ[8 * blk + 1], WQ[8 * blk + 2], WQ[8 * blk + 3], B.x, B.y);
                    mma(b, WQ[8 * blk + 4], WQ[8 * blk + 5], WQ[8 * blk + 6], WQ[8 * blk + 7], B.z, B.w);
                }
            }
            if (j < 2) st_async(jsb + OFF_Q + (8 * w + g) * 8 + r * 4, __float_as_uint((a[0] + b[0]) + (a[3] + b[3])), jsb + bar);
            TS(1, s * 16 + 4);
        }
        if (s >= 2 && p == OUT_PAIR) {
            const int b = s - 2;
            poll_residual<true>(acc + hop_off(4 * b + 3), CNT2, xcol + b * 640, j, 0, 0, b2v, x);
            if (j < 2) {
                uint16_t* o = reinterpret_cast<uint16_t*>(P.out) + b * DM + 320 * r + col;
                o[0] = (uint16_t)(__float_as_uint(x[0]) >> 16);
                o[8] = (uint16_t)(__float_as_uint(x[1]) >> 16);
                if (j == 0) o[16] = (uint16_t)(__float_as_uint(x[2]) >> 16);
            }
            __syncwarp();
            TS(1, b * 16 + 8);
        }
        if (s >= 1 && s <= NB && (active || p == OUT_PAIR)) {
            const int b = s - 1;
            poll_residual<false>(acc + hop_off(4 * b + 2), CNT1, xcol + b * 640, j, t0, POLL_DELAY, b2v, x);
            if (j < 2) { sts16(xcol + b * 640, x[0]); sts16(xcol + b * 640 + 16, x[1]); if (j == 0) sts16(xcol + b * 640 + 32, x[2]); }
            TS(1, b * 16 + 6);
            if (active) {
                chain_bar();
                stage_mlp(W1, W2, cs1, b1v, 1, s & 1, sb + OFF_X + b * 640, acc + hop_off(4 * b + 3), sb, jsb, r, w, lane);
            }
            TS(1, b * 16 + 7);
        }
    }
}

struct Maps { CUtensorMap k, v, wq, wo, w1, w2; };

__device__ __forceinline__ void issue_item(const Maps& M, int i, uint32_t sl, uint32_t sb, uint64_t pol) {
    const int c = blockIdx.x, r = c & 1, p = c >> 1;
    const uint32_t bar = sb + OFF_BAR + sl * 8, dst = sb + sl * SLOT;
    mbar_expect(bar, SLOT);
    if (i >= NWI) {
        const int ii = i - NWI;
        const int y = ((ii >> 4) * 32 + (c >> 2)) * SK + (SK - WIN) + r * 512 + (ii & 7) * 64;
        tma2d(dst, (ii & 8) ? &M.v : &M.k, (p & 1) * 64, y, bar, pol);
    } else if (i < 5) {
        tma2d(dst, &M.wq, 64 * p, 320 * r + 64 * i, bar, pol);
    } else if (i < 10) {
        tma2d(dst, &M.wo, 320 * r + 64 * (i - 5), 64 * p, bar, pol);
    } else {
        tma2d(dst, &M.w1, 32 * p, 320 * r + 64 * (i - 10), bar, pol);
        tma2d(dst + 4096, &M.w2, 320 * r + 64 * (i - 10), 32 * p, bar, pol);
    }
}

__global__ void __cluster_dims__(2, 1, 1) __launch_bounds__(NTHREADS, 1)
fused_decode_kernel(const __grid_constant__ Maps M, const __grid_constant__ Params P) {
    extern __shared__ __align__(1024) unsigned char smem[];
    const uint32_t sb = (uint32_t)__cvta_generic_to_shared(smem);
    const int tid = threadIdx.x, warp = tid >> 5, lane = tid & 31, c = blockIdx.x;
    const uint32_t bars = sb + OFF_BAR;
    uint32_t rsb;
    asm("mapa.shared::cluster.u32 %0, %1, %2;" : "=r"(rsb) : "r"(sb), "r"((c & 1) ^ 1));
    uint64_t pol = 0;
    if (warp == 12) {
        if (sb & 1023) __trap();
        if (lane < NSLOT) { mbar_init(bars + (BAR_FULL + lane) * 8, 1); mbar_init(bars + (BAR_EMPTY + lane) * 8, 4); }
        if (lane < 6) mbar_init(bars + (BAR_O + lane) * 8, 1);
        if (lane == 6 || lane == 7) mbar_init(bars + (BAR_O + lane) * 8, 8);
        if (lane == 8) mbar_init(bars + BAR_INIT * 8, 1);
        asm volatile("fence.mbarrier_init.release.cluster;" ::: "memory");
        __syncwarp();
        if (lane == 0) {
            asm volatile("createpolicy.fractional.L2::evict_first.b64 %0, 1.0;" : "=l"(pol));
            for (int i = 0; i < WINDOW; i++) issue_item(M, i, i, sb, pol);
        } else if (lane < 6) {
            const CUtensorMap* tm = lane == 1 ? &M.wo : lane == 2 ? &M.w1 : lane == 3 ? &M.w2 : lane == 4 ? &M.k : &M.v;
            asm volatile("prefetch.tensormap [%0];" ::"l"(tm) : "memory");
        } else if (lane < 12) {
            const int b = lane - 6;
            mbar_expect(bars + (BAR_O + b) * 8, b < 2 ? TX_O : b == 2 ? TX_H : b == 3 ? 512u : b == 4 ? TX_Q : TX_P);
        }
    }
    g_xch[c * 512 + tid] = make_uint4(0, 0, 0, 0);
    if (tid < 64) g_acc[c * 64 + tid] = make_uint4(0, 0, 0, 0);
    asm volatile("barrier.cluster.arrive.release.aligned;\nbarrier.cluster.wait.acquire.aligned;" ::: "memory");

    if (warp < 12) {
        asm volatile("setmaxnreg.inc.sync.aligned.u32 %0;" ::"n"(REG_WORK));
        if (warp < 4) attention_role(sb, rsb, warp, lane);
        else chain_role(P, sb, rsb, warp - 4, lane);
    } else {
        asm volatile("setmaxnreg.dec.sync.aligned.u32 %0;" ::"n"(REG_MISC));
        if (tid == 12 * 32) {
            uint32_t sl = WINDOW, use = 0, wsl = 0, wpar = 0;
#pragma unroll 1
            for (int i = WINDOW; i < NITEM; i++) {
                if (use) mbar_wait(bars + (BAR_EMPTY + sl) * 8, (use - 1) & 1);
                if (i == TMP_SLOT) mbar_wait(bars + BAR_TMP * 8, 0);
                mbar_wait(bars + wsl * 8, wpar);
                issue_item(M, i, sl, sb, pol);
                if (++sl == NSLOT) { sl = 0; use++; }
                if (++wsl == NSLOT) { wsl = 0; wpar ^= 1; }
            }
        } else if (tid == 13 * 32) {
            __threadfence();
            const unsigned target = (atomicAdd(&g_arrive, 1u) / NCTA + 1) * NCTA;
            int n = 0;
            while ((int)(*(volatile unsigned*)&g_arrive - target) < 0) { if (++n > 4000000) __trap(); }
            __threadfence();
            mbar_arrive(bars + BAR_INIT * 8);
        }
    }
}

typedef CUresult (*EncodeFn)(CUtensorMap*, CUtensorMapDataType, cuuint32_t, void*, const cuuint64_t*, const cuuint64_t*,
                             const cuuint32_t*, const cuuint32_t*, CUtensorMapInterleave, CUtensorMapSwizzle,
                             CUtensorMapL2promotion, CUtensorMapFloatOOBfill);

bool make_map(EncodeFn enc, CUtensorMap* m, const void* base, uint64_t cols, uint64_t rows, uint32_t bx, uint32_t by, bool swz) {
    cuuint64_t gd[2] = {cols, rows}, gs[1] = {cols * 2};
    cuuint32_t box[2] = {bx, by}, es[2] = {1, 1};
    return enc(m, CU_TENSOR_MAP_DATA_TYPE_BFLOAT16, 2, const_cast<void*>(base), gd, gs, box, es, CU_TENSOR_MAP_INTERLEAVE_NONE,
               swz ? CU_TENSOR_MAP_SWIZZLE_128B : CU_TENSOR_MAP_SWIZZLE_NONE, CU_TENSOR_MAP_L2_PROMOTION_L2_128B,
               CU_TENSOR_MAP_FLOAT_OOB_FILL_NONE) == CUDA_SUCCESS;
}

}

extern "C" void kernel_launch(void* const* d_in, const int* in_sizes, int n_in, void* d_out, int out_size) {
    (void)in_sizes; (void)n_in; (void)out_size;
    void* fn = nullptr;
    cudaDriverEntryPointQueryResult qr;
    if (cudaGetDriverEntryPoint("cuTensorMapEncodeTiled", &fn, cudaEnableDefault, &qr) != cudaSuccess || !fn) return;
    EncodeFn enc = (EncodeFn)fn;
    Maps M;
    bool ok = make_map(enc, &M.k, d_in[1], 128, (uint64_t)NB * 32 * SK, 64, 64, true) &&
              make_map(enc, &M.v, d_in[2], 128, (uint64_t)NB * 32 * SK, 64, 64, true) &&
              make_map(enc, &M.wq, d_in[3], 4096, DM, 64, 64, true) &&
              make_map(enc, &M.wo, d_in[4], DM, 4096, 64, 64, true) &&
              make_map(enc, &M.w1, d_in[6], FF, DM, 32, 64, false) &&
              make_map(enc, &M.w2, d_in[8], DM, FF, 64, 32, true);
    cudaFuncAttributes fa;
    ok = ok && cudaFuncGetAttributes(&fa, fused_decode_kernel) == cudaSuccess &&
         fa.numRegs * 4 >= 3 * REG_WORK + REG_MISC;
    if (!ok) return;
    cudaFuncSetAttribute(fused_decode_kernel, cudaFuncAttributeMaxDynamicSharedMemorySize, SMEM_BYTES);
    Params P;
    P.x = (const __nv_bfloat16*)d_in[0];
    P.b1 = (const __nv_bfloat16*)d_in[7];
    P.b2 = (const __nv_bfloat16*)d_in[9];
    P.out = (__nv_bfloat16*)d_out;
    fused_decode_kernel<<<NCTA, NTHREADS, SMEM_BYTES>>>(M, P);
}
```

```cpp
#include <cuda_runtime.h>
#include <cuda_bf16.h>
#include <cuda.h>
#include <stdint.h>

namespace {

constexpr int NB = 8, DM = 640, SK = 4096, WIN = 1024, FF = 1728;
constexpr int NCTA = 128, NTHREADS = 512;
constexpr int SLOT = 8192, NSLOT = 27, NWI = 15;
constexpr int TMP_SLOT = 25;
constexpr int ACT_PAIRS = FF / 32;
constexpr int OUT_PAIR = ACT_PAIRS;
#define HOLD 6
#define WINDOW 4
#define POLL_DELAY 400
#define SLEEP_WAIT 0
#define XCH1_DELAY 1400
#define WSTART 6
#define WSHRINK 5
#define TOUCH 1
#define PRE_BYTES 16384
#define LEAD_STEP 128
#define WMIN 3
#define WMAX 6
#define LEAD_BIAS 176
#define PACE_GAP 300
#define XCH_AT 14
constexpr int REG_WORK = 160, REG_MISC = 32;

constexpr int OFF_BAR = NSLOT * SLOT;
constexpr int BAR_EMPTY = NSLOT, BAR_O = 2 * NSLOT, BAR_H = BAR_O + 2, BAR_Q = BAR_H + 2,
              BAR_P = BAR_Q + 1, BAR_TMP = BAR_P + 1, BAR_Q1 = BAR_TMP + 1, BAR_INIT = BAR_Q1 + 1;
constexpr int OFF_PACE = OFF_BAR + 63 * 8;
constexpr int OFF_O = OFF_BAR + 512;
constexpr int OFF_ML = OFF_O + 2 * 8 * 144;
constexpr int OFF_H = OFF_ML + 128;
constexpr int OFF_Q = OFF_H + 2 * 560;
constexpr int OFF_Q1 = OFF_Q + 560;
constexpr int OFF_CSQ = OFF_Q1 + 1024;
constexpr int OFF_X = OFF_CSQ + 256;
constexpr int SMEM_BYTES = OFF_X + NB * 640 + 32;
static_assert(SMEM_BYTES <= 232448, "smem");
static_assert(BAR_INIT < 63, "barriers");
constexpr uint32_t TX_O = 8 * (128 + 8), TX_H = 2 * (256 + 24), TX_Q = 2 * (256 + 24), TX_P = 2 * 9 * 64 * 4;

constexpr float LN_EPS = 1e-5f;
constexpr float LOG2E = 1.4426950408889634f;
constexpr float SCALE = 0.08838834764831845f;
constexpr uint32_t ONES = 0x3F803F80u;

__device__ uint4 g_acc[32 * 256];
__device__ uint4 g_xch[NCTA * 4 * 128];
__device__ unsigned g_progress;
__device__ unsigned g_arrive;
#define TS(role, idx) do {} while (0)

__device__ __forceinline__ uint32_t clk32() { uint32_t c; asm volatile("mov.u32 %0, %%clock;" : "=r"(c)); return c; }
__device__ __forceinline__ void mbar_init(uint32_t bar, uint32_t cnt) {
    asm volatile("mbarrier.init.shared::cta.b64 [%0], %1;" ::"r"(bar), "r"(cnt) : "memory");
}
__device__ __forceinline__ void mbar_expect(uint32_t bar, uint32_t bytes) {
    asm volatile("mbarrier.arrive.expect_tx.shared::cta.b64 _, [%0], %1;" ::"r"(bar), "r"(bytes) : "memory");
}
__device__ __forceinline__ void mbar_arrive(uint32_t bar) {
    asm volatile("mbarrier.arrive.shared::cta.b64 _, [%0];" ::"r"(bar) : "memory");
}
__device__ __forceinline__ void mbar_expect_if(bool on, uint32_t bar, uint32_t bytes) {
    asm volatile("{\n.reg .pred p;\nsetp.ne.u32 p, %2, 0;\n@p mbarrier.arrive.expect_tx.shared::cta.b64 _, [%0], %1;\n}"
                 ::"r"(bar), "r"(bytes), "r"((uint32_t)on) : "memory");
}
__device__ __forceinline__ void mbar_arrive_if(bool on, uint32_t bar) {
    asm volatile("{\n.reg .pred p;\nsetp.ne.u32 p, %1, 0;\n@p mbarrier.arrive.shared::cta.b64 _, [%0];\n}" ::"r"(bar), "r"((uint32_t)on) : "memory");
}
__device__ __forceinline__ bool mbar_test(uint32_t bar, uint32_t parity) {
    uint32_t ok;
    asm volatile("{\n.reg .pred p;\nmbarrier.test_wait.parity.shared::cta.b64 p, [%1], %2;\nselp.u32 %0, 1, 0, p;\n}"
                 : "=r"(ok) : "r"(bar), "r"(parity) : "memory");
    return ok;
}
__device__ __forceinline__ void mbar_wait(uint32_t bar, uint32_t parity) {
    asm volatile(
        "{\n.reg .pred p;\n.reg .u32 n;\nmov.u32 n, 0;\n"
        "W_%=:\n"
        "mbarrier.try_wait.parity.shared::cta.b64 p, [%0], %1;\n"
        "@p bra.uni D_%=;\n"
        "add.u32 n, n, 1;\nsetp.lt.u32 p, n, 0x1000000;\n@p bra.uni W_%=;\ntrap;\n"
        "D_%=:\n}\n" ::"r"(bar), "r"(parity) : "memory");
}
__device__ __forceinline__ void mbar_wait_long(uint32_t bar, uint32_t parity) {
    mbar_wait(bar, parity);
}
__device__ __forceinline__ void st_async(uint32_t addr, uint32_t v, uint32_t bar) {
    asm volatile("st.async.shared::cluster.mbarrier::complete_tx::bytes.b32 [%0], %1, [%2];" ::"r"(addr), "r"(v), "r"(bar) : "memory");
}
__device__ __forceinline__ void st_async_if(bool on, uint32_t addr, uint32_t v, uint32_t bar) {
    asm volatile("{\n.reg .pred p;\nsetp.ne.u32 p, %3, 0;\n@p st.async.shared::cluster.mbarrier::complete_tx::bytes.b32 [%0], %1, [%2];\n}"
                 ::"r"(addr), "r"(v), "r"(bar), "r"((uint32_t)on) : "memory");
}
__device__ __forceinline__ void tma2d(uint32_t dst, const CUtensorMap* tm, int x, int y, uint32_t bar, uint64_t pol) {
    asm volatile("cp.async.bulk.tensor.2d.shared::cluster.global.mbarrier::complete_tx::bytes.L2::cache_hint [%0], [%1, {%3, %4}], [%2], %5;"
                 ::"r"(dst), "l"(tm), "r"(bar), "r"(x), "r"(y), "l"(pol) : "memory");
}
__device__ __forceinline__ void ldsm4(uint32_t& r0, uint32_t& r1, uint32_t& r2, uint32_t& r3, uint32_t a) {
    asm volatile("ldmatrix.sync.aligned.m8n8.x4.shared.b16 {%0,%1,%2,%3}, [%4];" : "=r"(r0), "=r"(r1), "=r"(r2), "=r"(r3) : "r"(a));
}
__device__ __forceinline__ void ldsm4t(uint32_t& r0, uint32_t& r1, uint32_t& r2, uint32_t& r3, uint32_t a) {
    asm volatile("ldmatrix.sync.aligned.m8n8.x4.trans.shared.b16 {%0,%1,%2,%3}, [%4];" : "=r"(r0), "=r"(r1), "=r"(r2), "=r"(r3) : "r"(a));
}
__device__ __forceinline__ void mma(float (&c)[4], uint32_t a0, uint32_t a1, uint32_t a2, uint32_t a3, uint32_t b0, uint32_t b1) {
    asm("mma.sync.aligned.m16n8k16.row.col.f32.bf16.bf16.f32 {%0,%1,%2,%3}, {%4,%5,%6,%7}, {%8,%9}, {%0,%1,%2,%3};"
        : "+f"(c[0]), "+f"(c[1]), "+f"(c[2]), "+f"(c[3]) : "r"(a0), "r"(a1), "r"(a2), "r"(a3), "r"(b0), "r"(b1));
}
__device__ __forceinline__ uint4 lds128(uint32_t a) {
    uint4 v; asm volatile("ld.shared.v4.b32 {%0,%1,%2,%3}, [%4];" : "=r"(v.x), "=r"(v.y), "=r"(v.z), "=r"(v.w) : "r"(a)); return v;
}
__device__ __forceinline__ float4 lds128f(uint32_t a) {
    float4 v; asm volatile("ld.shared.v4.f32 {%0,%1,%2,%3}, [%4];" : "=f"(v.x), "=f"(v.y), "=f"(v.z), "=f"(v.w) : "r"(a)); return v;
}
__device__ __forceinline__ uint2 lds64(uint32_t a) {
    uint2 v; asm volatile("ld.shared.v2.b32 {%0,%1}, [%2];" : "=r"(v.x), "=r"(v.y) : "r"(a)); return v;
}
__device__ __forceinline__ float2 lds64f(uint32_t a) {
    float2 v; asm volatile("ld.shared.v2.f32 {%0,%1}, [%2];" : "=f"(v.x), "=f"(v.y) : "r"(a)); return v;
}
__device__ __forceinline__ void sts32(uint32_t a, uint32_t v) { asm volatile("st.shared.b32 [%0], %1;" ::"r"(a), "r"(v) : "memory"); }
__device__ __forceinline__ uint32_t pack2(float lo, float hi) {
    uint32_t d; asm("cvt.rn.bf16x2.f32 %0, %1, %2;" : "=r"(d) : "f"(hi), "f"(lo)); return d;
}
__device__ __forceinline__ float rbf(float x) { return __uint_as_float(pack2(x, 0.f) << 16); }
__device__ __forceinline__ float ex2(float x) { float y; asm("ex2.approx.ftz.f32 %0, %1;" : "=f"(y) : "f"(x)); return y; }
__device__ __forceinline__ float fsqrt(float x) { float y; asm("sqrt.approx.f32 %0, %1;" : "=f"(y) : "f"(x)); return y; }
__device__ __forceinline__ float fdiv(float a, float b) { float y; asm("div.full.f32 %0, %1, %2;" : "=f"(y) : "f"(a), "f"(b)); return y; }
__device__ __forceinline__ float warp_max(float x) {
    int i = __float_as_int(x), m;
    i ^= (i >> 31) & 0x7fffffff;
    asm volatile("redux.sync.max.s32 %0, %1, 0xffffffff;" : "=r"(m) : "r"(i));
    m ^= (m >> 31) & 0x7fffffff;
    return __int_as_float(m);
}
__device__ __forceinline__ float warp_sum(float x) {
#pragma unroll
    for (int o = 16; o; o >>= 1) x += __shfl_xor_sync(0xffffffffu, x, o);
    return x;
}
__device__ __forceinline__ uint4 ld_relaxed(const uint4* p) {
    uint4 v; asm volatile("ld.relaxed.gpu.global.v4.b32 {%0,%1,%2,%3}, [%4];" : "=r"(v.x), "=r"(v.y), "=r"(v.z), "=r"(v.w) : "l"(p) : "memory");
    return v;
}
__device__ __forceinline__ float rcp(float x) { float y; asm("rcp.approx.ftz.f32 %0, %1;" : "=f"(y) : "f"(x)); return y; }
__device__ __forceinline__ float rsq(float x) { float y; asm("rsqrt.approx.ftz.f32 %0, %1;" : "=f"(y) : "f"(x)); return y; }
__device__ __forceinline__ int fresh_lane() { int l; asm volatile("mov.u32 %0, %%laneid;" : "=r"(l)); return l; }
__device__ __forceinline__ uint32_t badd2(uint32_t a, uint32_t b) { uint32_t d; asm("add.rn.bf16x2 %0, %1, %2;" : "=r"(d) : "r"(a), "r"(b)); return d; }
__device__ __forceinline__ uint32_t lds16(uint32_t a) { uint32_t v; asm volatile("ld.shared.u16 %0, [%1];" : "=r"(v) : "r"(a)); return v; }
__device__ __forceinline__ void spin_guard(int& n) { if (++n > 4000000) __trap(); }

struct Params {
    const __nv_bfloat16* x;
    const __nv_bfloat16* wq;
    const __nv_bfloat16* wo;
    const __nv_bfloat16* k;
    const __nv_bfloat16* v;
    const __nv_bfloat16* b1;
    const __nv_bfloat16* b2;
    __nv_bfloat16* out;
    uint32_t zero;
};

__device__ __forceinline__ void xch_send(uint32_t (&s)[4], uint4* dst, uint32_t tag) {
#pragma unroll
    for (int i = 0; i < 4; i++) s[i] = (s[i] & ~1u) | tag;
    asm volatile("st.relaxed.gpu.global.v4.b32 [%0], {%1,%2,%3,%4};" ::"l"(dst), "r"(s[0]), "r"(s[1]), "r"(s[2]), "r"(s[3]) : "memory");
}

__device__ __forceinline__ void xch_recv(uint4& v, const uint4* src, uint32_t tag) {
    int n = 0;
    while (__any_sync(0xffffffffu, (((v.x ^ tag) | (v.y ^ tag)) | ((v.z ^ tag) | (v.w ^ tag))) & 1u)) {
        v = ld_relaxed(src);
        spin_guard(n);
    }
}
template <bool ROUND>
__device__ __forceinline__ void softmax4(const uint32_t (&s)[4], const uint4& v, uint32_t& P0, uint32_t& P1, float& m, float& l) {
    float t[4] = {__uint_as_float(s[0]) + __uint_as_float(v.x), __uint_as_float(s[1]) + __uint_as_float(v.y),
                  __uint_as_float(s[2]) + __uint_as_float(v.z), __uint_as_float(s[3]) + __uint_as_float(v.w)};
#pragma unroll
    for (int i = 0; i < 4; i++) t[i] = ROUND ? rbf(rbf(t[i]) * SCALE) * LOG2E : t[i] * (SCALE * LOG2E);
    m = warp_max(fmaxf(fmaxf(t[0], t[1]), fmaxf(t[2], t[3])));
#pragma unroll
    for (int i = 0; i < 4; i++) t[i] = ex2(t[i] - m);
    P0 = pack2(t[0], t[1]);
    P1 = pack2(t[2], t[3]);
    l = (t[0] + t[1]) + (t[2] + t[3]);
}

__device__ __forceinline__ void publish_o(const float (&o)[4][4], float m, float l, int k, uint32_t sb, uint32_t rsb,
                                          int src, int lane) {
    const int g = lane >> 2, j = lane & 3;
    float lo = (j & 2) ? ((j & 1) ? o[3][0] : o[2][0]) : ((j & 1) ? o[1][0] : o[0][0]);
    float hi = (j & 2) ? ((j & 1) ? o[3][2] : o[2][2]) : ((j & 1) ? o[1][2] : o[0][2]);
    uint32_t wd = pack2(lo, hi);
    uint32_t off = OFF_O + k * (8 * 144) + src * 144 + (8 * j + ((g - 2 * j) & 7)) * 4, bar = OFF_BAR + (BAR_O + k) * 8;
    st_async(rsb + off, wd, rsb + bar);
    st_async(sb + off, wd, sb + bar);
    uint32_t base = (lane & 2) ? sb : rsb;
    st_async_if(lane < 4, base + OFF_ML + k * 64 + src * 8 + (lane & 1) * 4, __float_as_uint((lane & 1) ? l : m), base + bar);
}

__device__ __forceinline__ uint32_t next_slot(uint32_t sl) { return sl == NSLOT - 1 ? 0 : sl + 1; }
template <int N>
__device__ __forceinline__ uint32_t release_slots(uint32_t bars, uint32_t sl, int lane, const uint32_t* frag, uint32_t zero) {
    uint32_t dep = 0;
#pragma unroll
    for (int i = 0; i < 4 * N; i++) dep |= frag[4 * i];
    uint32_t t = sl + lane;
    if (t >= NSLOT) t -= NSLOT;
    mbar_arrive_if(lane < N, bars + (BAR_EMPTY + t) * 8 + (dep & zero));
    return sl + N >= NSLOT ? sl + N - NSLOT : sl + N;
}

__device__ __forceinline__ void attention_role(uint32_t sb, uint32_t rsb, int w, int lane0, uint32_t zero) {
    const int c = blockIdx.x, r = c & 1;
    const int mi = lane0 >> 3, i8 = lane0 & 7;
    const uint32_t bars = sb + OFF_BAR;
    uint32_t koff, voff;
    {
        int row = 16 * w + ((mi & 1) ? 8 + ((i8 + 4) & 7) : i8);
        koff = sb + row * 128 + (((mi >> 1) ^ (row & 7)) << 4);
        int gi = (i8 >> 1) + 4 * (mi >> 1);
        row = 16 * w + ((i8 & 1) ? 8 + ((gi + 4) & 7) : gi);
        voff = sb + row * 128 + (((mi & 1) ^ (row & 7)) << 4);
    }
    uint4* const xin = g_xch + c * 512 + w * 32 + lane0;
    const int xo = (c & 2) ? -1024 : 1024;
    uint32_t hold[HOLD * 16];
#pragma unroll
    for (int i = 0; i < HOLD * 16; i++) hold[i] = 0;

    mbar_wait(bars + BAR_Q1 * 8, 0);

    uint32_t ksl = NWI, kpar = 0;
    uint32_t psl = 0;
#pragma unroll 1
    for (int s = -1; s < NB; ++s) {
        const int n = s + 1;
        const uint32_t tag1 = ((n >> 1) & 1) ^ 1, tag2 = ((s >> 1) & 1) ^ 1;
        uint32_t sl = ksl, par = kpar, s1[4] = {0, 0, 0, 0};
        if (n < NB) {
            const int lane = fresh_lane(), j = lane & 3;
            uint4 qa = lds128(sb + OFF_Q1 + n * 128 + j * 32), qb = lds128(sb + OFF_Q1 + n * 128 + j * 32 + 16);
#pragma unroll 1
            for (int cp = 0; cp < 4; cp++) {
                uint32_t base[2];
#pragma unroll
                for (int h = 0; h < 2; h++) {
                    mbar_wait_long(bars + sl * 8, par);
                    base[h] = koff + sl * SLOT;
                    if (++sl == NSLOT) { sl = 0; par ^= 1; }
                }
#pragma unroll
                for (int h = 0; h < 2; h++) {
                    uint32_t a[16];
                    float acc[4] = {0.f, 0.f, 0.f, 0.f}, acd[4] = {0.f, 0.f, 0.f, 0.f};
#pragma unroll
                    for (int ks = 0; ks < 4; ks++) ldsm4(a[4 * ks], a[4 * ks + 1], a[4 * ks + 2], a[4 * ks + 3], base[h] ^ (ks << 5));
                    mma(acc, a[0], a[1], a[2], a[3], qa.x, qa.y);
                    mma(acd, a[4], a[5], a[6], a[7], qa.z, qa.w);
                    mma(acc, a[8], a[9], a[10], a[11], qb.x, qb.y);
                    mma(acd, a[12], a[13], a[14], a[15], qb.z, qb.w);
                    if (j == cp) { s1[2 * h] = __float_as_uint(acc[0] + acd[0]); s1[2 * h + 1] = __float_as_uint(acc[2] + acd[2]); }
                }
            }
            if (n == 0) mbar_wait(bars + BAR_INIT * 8, 0);
            xch_send(s1, xin + (xo + (n & 1) * 128), tag1);
            TS(0, n * 16 + 0);
        }
        uint32_t s2[4], P0, P1;
        uint4 v2;
        float m1, l1;
        if (s >= 0) {
            const int lane = fresh_lane(), j = lane & 3;
            const uint32_t t0 = clk32();
            uint32_t a[(8 - HOLD) * 16], qf[8];
            uint32_t t = psl;
#pragma unroll
            for (int i = 0; i < 8 - HOLD; i++) {
#pragma unroll
                for (int ks = 0; ks < 4; ks++) {
                    const int q = i * 16 + ks * 4;
                    ldsm4(a[q], a[q + 1], a[q + 2], a[q + 3], (koff + t * SLOT) ^ (ks << 5));
                }
                t = next_slot(t);
            }
            psl = release_slots<8 - HOLD>(bars, psl, lane, a, zero);
            while (clk32() - t0 < XCH1_DELAY && !mbar_test(bars + BAR_Q * 8, s & 1)) {}
            uint4 v1 = ld_relaxed(xin + (n & 1) * 128);
            mbar_wait_long(bars + BAR_Q * 8, s & 1);
            TS(0, s * 16 + 4);
            {
                float4 su = lds128f(sb + OFF_Q + 544), sa = lds128f(sb + OFF_Q + 512), sc = lds128f(sb + OFF_Q + 528);
                float4 pq = lds128f(sb + OFF_Q + lane * 16);
                float2 cs = lds64f(sb + OFF_CSQ + lane * 8);
                mbar_expect_if(w + lane == 0, bars + BAR_Q * 8, TX_Q);
                float mean = ((su.x + su.y) + (su.z + su.w)) * (1.f / DM);
                float var = fmaxf((((sa.x + sa.y) + (sa.z + sa.w)) + ((sc.x + sc.y) + (sc.z + sc.w))) * (1.f / DM) - mean * mean, 0.f);
                float rs = rsq(var + LN_EPS);
                uint32_t pk = pack2((pq.x + pq.y - mean * cs.x) * rs, (pq.z + pq.w - mean * cs.y) * rs);
#pragma unroll
                for (int i = 0; i < 8; i++) qf[i] = i ? __shfl_xor_sync(0xffffffffu, pk, 4 * i) : pk;
            }
#pragma unroll
            for (int ch = 0; ch < 8; ch++) {
                const int qx = ch >> 1;
                const uint32_t* kf = ch < HOLD ? hold + ch * 16 : a + (ch - HOLD) * 16;
                float acc[4] = {0.f, 0.f, 0.f, 0.f};
#pragma unroll
                for (int i = 0; i < 4; i++) {
                    const int ks = i ^ qx;
                    mma(acc, kf[4 * ks], kf[4 * ks + 1], kf[4 * ks + 2], kf[4 * ks + 3], qf[2 * i], qf[2 * i + 1]);
                }
                if (ch < 2 || j == qx) { s2[(ch & 1) * 2] = __float_as_uint(acc[0]); s2[(ch & 1) * 2 + 1] = __float_as_uint(acc[2]); }
            }
            xch_send(s2, xin + (xo + (2 + (s & 1)) * 128), tag2);
            TS(0, s * 16 + 5);
            if (n < NB) xch_recv(v1, xin + (n & 1) * 128, tag1);
            t = psl;
#pragma unroll
            for (int i = 0; i < HOLD; i++) {
                const uint32_t base = voff + t * SLOT;
#pragma unroll
                for (int mt = 0; mt < 4; mt++) {
                    const int q = i * 16 + mt * 4;
                    ldsm4t(hold[q], hold[q + 1], hold[q + 2], hold[q + 3], base ^ (mt << 5));
                }
                t = next_slot(t);
            }
            softmax4<true>(s1, v1, P0, P1, m1, l1);
            psl = release_slots<2>(bars, psl, lane, hold, zero);
            v2 = ld_relaxed(xin + ((2 + (s & 1)) * 128 + (hold[4 * XCH_AT] & zero)));
            psl = release_slots<HOLD - 2>(bars, psl, lane, hold + 32, zero);
            TS(0, s * 16 + 6);
        } else {
            __nanosleep(600);
            uint4 v1 = ld_relaxed(xin);
            xch_recv(v1, xin, tag1);
            softmax4<true>(s1, v1, P0, P1, m1, l1);
            s2[0] = s2[1] = s2[2] = s2[3] = 0;
            v2 = make_uint4(0, 0, 0, 0);
        }
        float o[4][4];
        if (n < NB) {
            const int lane = fresh_lane(), j4 = (lane & 3) * 4;
            uint32_t a[16];
#pragma unroll
            for (int mt = 0; mt < 4; mt++) o[mt][0] = o[mt][1] = o[mt][2] = o[mt][3] = 0.f;
            uint32_t b0 = __shfl_sync(0xffffffffu, P0, j4), b1 = __shfl_sync(0xffffffffu, P0, j4 + 16);
            mbar_wait_long(bars + sl * 8, par);
#pragma unroll
            for (int mt = 0; mt < 4; mt++) ldsm4t(a[4 * mt], a[4 * mt + 1], a[4 * mt + 2], a[4 * mt + 3], (voff + sl * SLOT) ^ (mt << 5));
            if (++sl == NSLOT) { sl = 0; par ^= 1; }
            bool here = mbar_test(bars + sl * 8, par);
#pragma unroll 1
            for (int u = 1; u < 8; u++) {
                const uint32_t base = voff + sl * SLOT, P = (u & 1) ? P1 : P0;
                if (!here) mbar_wait_long(bars + sl * 8, par);
                if (++sl == NSLOT) { sl = 0; par ^= 1; }
                here = mbar_test(bars + sl * 8, par);
                const uint32_t n0 = __shfl_sync(0xffffffffu, P, j4 + (u >> 1)), n1 = __shfl_sync(0xffffffffu, P, j4 + 16 + (u >> 1));
#pragma unroll
                for (int mt = 0; mt < 4; mt++) {
                    mma(o[mt], a[4 * mt], a[4 * mt + 1], a[4 * mt + 2], a[4 * mt + 3], b0, b1);
                    ldsm4t(a[4 * mt], a[4 * mt + 1], a[4 * mt + 2], a[4 * mt + 3], base ^ (mt << 5));
                }
                b0 = n0; b1 = n1;
                const float lo = __shfl_xor_sync(0xffffffffu, l1, 32 >> u);
                if (u <= 5) l1 += lo;
            }
#pragma unroll
            for (int mt = 0; mt < 4; mt++) mma(o[mt], a[4 * mt], a[4 * mt + 1], a[4 * mt + 2], a[4 * mt + 3], b0, b1);
            publish_o(o, m1, l1, 0, sb, rsb, 4 * r + w, lane);
            TS(0, n * 16 + 2);
        }
        if (s >= 0) {
            const int lane = fresh_lane(), j = lane & 3;
            uint32_t a[16];
#pragma unroll
            for (int mt = 0; mt < 4; mt++) ldsm4t(a[4 * mt], a[4 * mt + 1], a[4 * mt + 2], a[4 * mt + 3], (voff + psl * SLOT) ^ (mt << 5));
            psl = release_slots<1>(bars, psl, lane, a, zero);
            float m, l;
            xch_recv(v2, xin + (2 + (s & 1)) * 128, tag2);
            softmax4<false>(s2, v2, P0, P1, m, l);
            TS(0, s * 16 + 7);
#pragma unroll
            for (int mt = 0; mt < 4; mt++) o[mt][0] = o[mt][1] = o[mt][2] = o[mt][3] = 0.f;
#pragma unroll
            for (int t = 0; t < 8; t++) {
                const int u = t == 0 ? HOLD : t <= HOLD ? t - 1 : t;
                uint32_t b0 = __shfl_sync(0xffffffffu, (u & 1) ? P1 : P0, 4 * j + (u >> 1));
                uint32_t b1 = __shfl_sync(0xffffffffu, (u & 1) ? P1 : P0, 4 * j + 16 + (u >> 1));
                if (u < HOLD) {
#pragma unroll
                    for (int mt = 0; mt < 4; mt++) {
                        const int q = (u < HOLD ? u : 0) * 16 + mt * 4;
                        mma(o[mt], hold[q], hold[q + 1], hold[q + 2], hold[q + 3], b0, b1);
                    }
                } else {
                    if (u > HOLD) psl = release_slots<1>(bars, psl, lane, a, zero);
#pragma unroll
                    for (int mt = 0; mt < 4; mt++) mma(o[mt], a[4 * mt], a[4 * mt + 1], a[4 * mt + 2], a[4 * mt + 3], b0, b1);
                    if (u < 7) {
#pragma unroll
                        for (int mt = 0; mt < 4; mt++) ldsm4t(a[4 * mt], a[4 * mt + 1], a[4 * mt + 2], a[4 * mt + 3], (voff + psl * SLOT) ^ (mt << 5));
                    }
                }
                if (t >= 1 && t <= 5) l += __shfl_xor_sync(0xffffffffu, l, 32 >> t);
            }
            publish_o(o, m, l, 1, sb, rsb, 4 * r + w, lane);
            TS(0, s * 16 + 8);
        }
        if (n < NB) {
            const int lane = fresh_lane();
            uint32_t t = ksl;
#pragma unroll
            for (int ch = 0; ch < HOLD; ch++) {
                const uint32_t base = koff + t * SLOT;
#pragma unroll
                for (int ks = 0; ks < 4; ks++) {
                    const int o = ch * 16 + ks * 4;
                    ldsm4(hold[o], hold[o + 1], hold[o + 2], hold[o + 3], base ^ (ks << 5));
                }
                t = next_slot(t);
            }
            psl = release_slots<HOLD>(bars, ksl, lane, hold, zero);
            TS(0, n * 16 + 3);
        }
        ksl = sl; kpar = par;
    }
}

__device__ __forceinline__ void chain_bar(uint32_t dep) { asm volatile("bar.sync %0, 256;" ::"r"(1 + dep) : "memory"); }
__device__ __forceinline__ void x_bar() { asm volatile("bar.sync 2, 288;" ::: "memory"); }

template <int OFF>
__device__ __forceinline__ void red_out(bool on, const uint4* p, const float (&v)[3]) {
    asm volatile("{\n.reg .pred p;\nsetp.ne.u32 p, %6, 0;\n@p red.relaxed.gpu.global.add.v4.f32 [%0+%5], {%1,%2,%3,%4};\n}"
                 ::"l"(p), "f"(v[0]), "f"(v[1]), "f"(v[2]), "f"(1.0f), "n"(OFF), "r"((uint32_t)on) : "memory");
}

template <int OFF>
__device__ __forceinline__ void poll_sum(const uint4* p, float count, uint32_t& y01, uint32_t& y2x) {
    float4 v; int n = 0;
    while (true) {
        asm volatile("ld.relaxed.gpu.global.v4.f32 {%0,%1,%2,%3}, [%4+%5];" : "=f"(v.x), "=f"(v.y), "=f"(v.z), "=f"(v.w) : "l"(p), "n"(OFF) : "memory");
        if (__all_sync(0xffffffffu, v.w == count)) break;
        spin_guard(n);
    }
    y01 = pack2(v.x, v.y); y2x = pack2(v.z, 0.f);
}
template <int OFF, bool BIAS>
__device__ __forceinline__ void poll_residual(const uint4* p, float count, uint32_t xrow, int w, uint32_t t0, uint32_t b01, uint32_t b2x) {
    const int lane = fresh_lane();
    const uint32_t xa = xrow + w * 80 + (lane & 1) * 48 + (lane >> 2) * 2;
    uint32_t x01 = lds16(xa) | (lds16(xa + 16) << 16), x2x = lds16(xa + 32), y01, y2x;
    while (clk32() - t0 < POLL_DELAY) {}
    poll_sum<OFF>(p, count, y01, y2x);
    if (BIAS) { y01 = badd2(y01, b01); y2x = badd2(y2x, b2x); }
    x01 = badd2(x01, y01); x2x = badd2(x2x, y2x);
    asm volatile("{\n.reg .pred p;\n.reg .b16 a, b, c, d;\nsetp.eq.u32 p, %3, 0;\nmov.b32 {a, b}, %1;\nmov.b32 {c, d}, %2;\n"
                 "st.shared.b16 [%0], a;\nst.shared.b16 [%0+16], b;\n@p st.shared.b16 [%0+32], c;\n}"
                 ::"r"(xa), "r"(x01), "r"(x2x), "r"(lane & 1) : "memory");
}

template <int K, int OFF>
__device__ __forceinline__ void stage_wo(const uint32_t (&WO)[40], uint32_t par, const uint4* acc, uint32_t sb, int w) {
    const int lane = fresh_lane(), g = lane >> 2, j = lane & 3;
    const uint32_t ob = sb + OFF_O + K * (8 * 144) + g * 144 + j * 32, ml = sb + OFF_ML + K * 64 + j * 16;
    mbar_wait_long(sb + OFF_BAR + (BAR_O + K) * 8, par);
    uint4 B0 = lds128(ob);
    float4 mm = lds128f(ml);
    uint4 B1 = lds128(ob + 16);
    mbar_expect_if(w + lane == 0, sb + OFF_BAR + (BAR_O + K) * 8, TX_O);
    const uint32_t B[8] = {B0.x, B0.y, B0.z, B0.w, B1.x, B1.y, B1.z, B1.w};
    float t0[4] = {0.f, 0.f, 0.f, 0.f}, t1[4] = {0.f, 0.f, 0.f, 0.f}, t2[4] = {0.f, 0.f, 0.f, 0.f}, t3[4] = {0.f, 0.f, 0.f, 0.f};
#pragma unroll
    for (int s = 0; s < 4; s++) {
        mma(t0, WO[4 * s], WO[4 * s + 1], WO[4 * s + 2], WO[4 * s + 3], B[2 * s], B[2 * s + 1]);
        mma(t1, WO[16 + 4 * s], WO[16 + 4 * s + 1], WO[16 + 4 * s + 2], WO[16 + 4 * s + 3], B[2 * s], B[2 * s + 1]);
        mma((s & 1) ? t3 : t2, WO[32 + 2 * (s & 2)], WO[33 + 2 * (s & 2)], WO[34 + 2 * (s & 2)], WO[35 + 2 * (s & 2)], B[2 * s], B[2 * s + 1]);
    }
    float M = fmaxf(mm.x, mm.z);
    M = fmaxf(M, __shfl_xor_sync(0xffffffffu, M, 1));
    M = fmaxf(M, __shfl_xor_sync(0xffffffffu, M, 2));
    const float e0 = ex2(mm.x - M), e1 = ex2(mm.z - M);
    float L = e0 * mm.y + e1 * mm.w;
    L += __shfl_xor_sync(0xffffffffu, L, 1);
    L += __shfl_xor_sync(0xffffffffu, L, 2);
    const float inv = rcp(L);
    float v[6] = {e0 * t0[0] + e1 * t0[1], e0 * t0[2] + e1 * t0[3], e0 * t1[0] + e1 * t1[1],
                  e0 * t1[2] + e1 * t1[3], e0 * (t2[0] + t3[2]) + e1 * (t2[1] + t3[3]), 0.f};
    float u[3];
    const bool odd = j & 1;
#pragma unroll
    for (int i = 0; i < 3; i++) u[i] = (odd ? v[3 + i] : v[i]) + __shfl_xor_sync(0xffffffffu, odd ? v[i] : v[3 + i], 1);
#pragma unroll
    for (int i = 0; i < 3; i++) u[i] = (u[i] + __shfl_xor_sync(0xffffffffu, u[i], 2)) * inv;
    red_out<OFF>(j < 2, acc, u);
}

template <int K, int OFF>
__device__ __forceinline__ void stage_mlp(const uint32_t (&W1)[20], const uint32_t (&W2)[20], float cs1, uint32_t b2x, uint32_t par,
                                          uint32_t xrow, const uint4* acc, uint32_t sb, uint32_t rsb, int r, int w, int lane) {
    const int g = lane >> 2, j = lane & 3, ht = w & 3, kh = w >> 2;
    const uint32_t xb = xrow + (g & 1) * 320 + j * 16;
    const uint32_t jsb = (j & 1) ? rsb : sb;
    constexpr uint32_t hb = OFF_H + K * 560, bar = OFF_BAR + (BAR_H + K) * 8;
    x_bar();
    uint4 B0 = lds128(xb + kh * 192);
    uint2 B2 = lds64(xb + 128 + kh * 8);
    uint4 B1 = lds128(xb + kh * 192 + 64);
    float a[4] = {0.f, 0.f, 0.f, 0.f}, b[4] = {0.f, 0.f, 0.f, 0.f}, d[4] = {0.f, 0.f, 0.f, 0.f};
    mma(a, W1[0], W1[1], W1[2], W1[3], B0.x, B0.y);
    mma(b, W1[4], W1[5], W1[6], W1[7], B0.z, B0.w);
    mma(d, W1[16], W1[17], W1[18], W1[19], B2.x, B2.y);
    mma(a, W1[8], W1[9], W1[10], W1[11], B1.x, B1.y);
    mma(b, W1[12], W1[13], W1[14], W1[15], B1.z, B1.w);
    st_async_if(j < 2, jsb + hb + (8 * ht + g) * 16 + (2 * r + kh) * 4, __float_as_uint(((d[0] + d[3]) + (a[0] + a[3])) + (b[0] + b[3])), jsb + bar);
    mbar_wait(sb + bar, par);
    float4 su = lds128f(sb + hb + 544), q0 = lds128f(sb + hb + 512), q1 = lds128f(sb + hb + 528), hp = lds128f(sb + hb + lane * 16);
    mbar_expect_if(w + lane == 0, sb + bar, TX_H);
    float mean = ((su.x + su.y) + (su.z + su.w)) * (1.f / DM);
    float var = fmaxf((((q0.x + q0.y) + (q0.z + q0.w)) + ((q1.x + q1.y) + (q1.z + q1.w))) * (1.f / DM) - mean * mean, 0.f);
    float rs = rsq(fmaf(var, 1.f + LN_EPS, LN_EPS * LN_EPS));
    float pre = __uint_as_float(badd2(pack2(0.f, (((hp.x + hp.y) + (hp.z + hp.w)) - mean * cs1) * rs), b2x) & 0xffff0000u);
    float u2 = pre * fmaf(pre * pre, -2.f * LOG2E * 0.7978845608028654f * 0.044715f, -2.f * LOG2E * 0.7978845608028654f);
    float h0 = pre * rcp(1.f + ex2(u2));
    float h1 = __shfl_xor_sync(0xffffffffu, h0, 8), h2 = __shfl_xor_sync(0xffffffffu, h0, 16), h3 = __shfl_xor_sync(0xffffffffu, h0, 24);
    const uint32_t b0 = pack2(h0, h1), b1 = pack2(h2, h3);
    float v[5];
#pragma unroll
    for (int e = 0; e < 5; e++) {
        float t[4] = {0.f, 0.f, 0.f, 0.f};
        mma(t, W2[4 * e], W2[4 * e + 1], W2[4 * e + 2], W2[4 * e + 3], b0, b1);
        v[e] = t[0] + t[3];
    }
    const bool odd = j & 1;
    float u[3] = {odd ? v[3] : v[0], odd ? v[4] : v[1], odd ? 0.f : v[2]};
    red_out<OFF>(j < 2, acc, u);
}

__device__ __forceinline__ void chain_role(const Params& P, uint32_t sb, uint32_t rsb, int w, int lane) {
    const int c = blockIdx.x, r = c & 1, p = c >> 1;
    const int g = lane >> 2, j = lane & 3, mi = lane >> 3, ri = lane & 7;
    const uint32_t bars = sb + OFF_BAR;
    const uint32_t jsb = (j & 1) ? rsb : sb;
    const bool active = p < ACT_PAIRS, odd = j & 1;
    uint32_t WQ[40], WO[40], W1[20], W2[20];

    {
        const uint32_t* xr = reinterpret_cast<const uint32_t*>(P.x + w * DM);
        uint32_t xw[10];
#pragma unroll
        for (int i = 0; i < 10; i++) xw[i] = __ldg(xr + lane + 32 * i);
        float sum = 0.f;
#pragma unroll
        for (int i = 0; i < 10; i++) sum += __uint_as_float(xw[i] << 16) + __uint_as_float(xw[i] & 0xffff0000u);
        const float mean = warp_sum(sum) * (1.f / DM);
        float sq = 0.f;
#pragma unroll
        for (int i = 0; i < 10; i++) {
            float d0 = __uint_as_float(xw[i] << 16) - mean, d1 = __uint_as_float(xw[i] & 0xffff0000u) - mean;
            sq += d0 * d0 + d1 * d1;
        }
        const float mb = rbf(mean), den = rbf(fsqrt(rbf(rbf(warp_sum(sq) * (1.f / DM)) + LN_EPS)));
#pragma unroll
        for (int i = 0; i < 5; i++) {
            uint32_t v = r ? xw[5 + i] : xw[i];
            float d0 = rbf(__uint_as_float(v << 16) - mb), d1 = rbf(__uint_as_float(v & 0xffff0000u) - mb);
            sts32(sb + OFF_X + w * 640 + (lane + 32 * i) * 4, v);
            sts32(sb + TMP_SLOT * SLOT + w * 640 + (lane + 32 * i) * 4, pack2(fdiv(d0, den), fdiv(d1, den)));
        }
    }
    const int col = 40 * w + 24 * (j & 1) + g;
    uint32_t b01, b2x;
    {
        const uint16_t* pb2 = reinterpret_cast<const uint16_t*>(P.b2) + 320 * r + col;
        b01 = (uint32_t)pb2[0] | ((uint32_t)pb2[8] << 16);
        b2x = (odd ? 0u : (uint32_t)pb2[16]) | (active ? (uint32_t)reinterpret_cast<const uint16_t*>(P.b1)[32 * p + lane] << 16 : 0u);
    }
#pragma unroll 1
    for (int i = 0; i < 5; i++) mbar_wait(bars + i * 8, 0);
#pragma unroll
    for (int t = 0; t < 10; t++) {
        int k = (mi & 1) * 160 + 32 * (t >> 1) + 8 * (ri >> 1) + 2 * (2 * (t & 1) + (mi >> 1)) + (ri & 1);
        ldsm4t(WQ[4 * t], WQ[4 * t + 1], WQ[4 * t + 2], WQ[4 * t + 3], sb + k * 128 + ((w ^ (k & 7)) << 4));
    }
    uint32_t dep = 0;
#pragma unroll
    for (int t = 0; t < 10; t++) dep |= WQ[4 * t];
    TS(1, 200);
    chain_bar(dep & P.zero);
    mbar_arrive_if(w < 4 && lane < 5, bars + (BAR_EMPTY + lane) * 8);
    {
        const uint32_t px = (TMP_SLOT + 1) * SLOT, pb = OFF_BAR + BAR_P * 8;
#pragma unroll 1
        for (int rd = 0; rd < 3; rd++) {
            const uint32_t xb = sb + TMP_SLOT * SLOT + (4 * (rd & 1) + (g >> 1)) * 640 + ((g & 1) * 160 + 8 * j) * 2;
            float a[4] = {0.f, 0.f, 0.f, 0.f};
#pragma unroll
            for (int blk = 0; blk < 5; blk++) {
                uint4 B = lds128(xb + blk * 64);
                if (rd == 2) B = make_uint4(ONES, ONES, ONES, ONES);
                mma(a, WQ[8 * blk], WQ[8 * blk + 1], WQ[8 * blk + 2], WQ[8 * blk + 3], B.x, B.y);
                mma(a, WQ[8 * blk + 4], WQ[8 * blk + 5], WQ[8 * blk + 6], WQ[8 * blk + 7], B.z, B.w);
            }
            uint32_t off = px + ((4 * rd + j) * 64 + 8 * w + g) * 8 + r * 4;
            st_async_if(rd < 2 || j == 0, sb + off, __float_as_uint(a[0] + a[3]), sb + pb);
            st_async_if(rd < 2 || j == 0, rsb + off, __float_as_uint(a[0] + a[3]), rsb + pb);
        }
        mbar_wait(sb + pb, 0);
        float4 v = lds128f(sb + px + w * 512 + lane * 16);
        sts32(sb + OFF_Q1 + w * 128 + ((lane & 3) * 8 + (lane >> 2)) * 4, pack2(v.x + v.y, v.z + v.w));
        float2 cs = lds64f(sb + px + 8 * 512 + (8 * w + ri) * 8);
        sts32(sb + OFF_CSQ + (8 * w + ri) * 4, __float_as_uint(cs.x + cs.y));
        asm volatile("fence.proxy.async.shared::cta;" ::: "memory");
        __syncwarp();
        mbar_arrive_if(lane < 2, bars + (BAR_TMP + lane) * 8);
    }
    TS(1, 201);
#pragma unroll 1
    for (int i = 5; i < 15; i++) mbar_wait(bars + i * 8, 0);
#pragma unroll
    for (int t = 0; t < 10; t++) {
        int cc = 5 * w + (t < 8 ? 2 * (t >> 2) + (mi & 1) : 4);
        int k = 16 * (ri >> 1) + 8 * (ri & 1) + (((t < 8 ? 2 * (t & 3) : 4 * (t - 8) + 2 * (mi & 1)) + (mi >> 1) + (ri & 6)) & 7);
        ldsm4t(WO[4 * t], WO[4 * t + 1], WO[4 * t + 2], WO[4 * t + 3],
               sb + (5 + (cc >> 3)) * SLOT + k * 128 + (((cc & 7) ^ (k & 7)) << 4));
    }
#pragma unroll
    for (int t = 0; t < 5; t++) {
        int k = (mi & 1) * 160 + 8 * (ri >> 1) + 2 * (mi >> 1) + (ri & 1) +
                (t < 4 ? (w >> 2) * 96 + 32 * (t >> 1) + 4 * (t & 1) : 64 + 4 * (w >> 2));
        ldsm4t(W1[4 * t], W1[4 * t + 1], W1[4 * t + 2], W1[4 * t + 3], sb + (10 + (k >> 6)) * SLOT + (k & 63) * 64 + (w & 3) * 16);
        int cc = 5 * w + t, k2 = 4 * (mi & 1) + (ri >> 1) + 8 * ((2 * (mi >> 1) + (ri & 1)) ^ (t >= 3));
        ldsm4t(W2[4 * t], W2[4 * t + 1], W2[4 * t + 2], W2[4 * t + 3],
               sb + (10 + (cc >> 3)) * SLOT + 4096 + k2 * 128 + (((cc & 7) ^ (k2 & 7)) << 4));
    }
#pragma unroll
    for (int t = 0; t < 10; t++) dep |= WO[4 * t] | (t < 5 ? W1[4 * (t % 5)] : W2[4 * (t % 5)]);
    chain_bar(dep & P.zero);
    TS(1, 202);
    mbar_arrive_if(w < 4 && lane < 10, bars + (BAR_EMPTY + 5 + lane) * 8);
    float cs1;
    {
        float a[4] = {0.f, 0.f, 0.f, 0.f};
#pragma unroll
        for (int t = 0; t < 5; t++) mma(a, W1[4 * t], W1[4 * t + 1], W1[4 * t + 2], W1[4 * t + 3], ONES, ONES);
        const uint32_t hb = OFF_H + 560, bar = OFF_BAR + (BAR_H + 1) * 8;
        st_async_if(j < 2, jsb + hb + (8 * (w & 3) + g) * 16 + (2 * r + (w >> 2)) * 4, __float_as_uint(a[0] + a[3]), jsb + bar);
        mbar_wait(sb + bar, 0);
        float4 hp = lds128f(sb + hb + lane * 16);
        mbar_expect_if(w + lane == 0, sb + bar, TX_H);
        cs1 = (hp.x + hp.y) + (hp.z + hp.w);
    }
    const uint4* acc = g_acc + (r * 16 + 2 * w + (g >> 2)) * 256 + ((2 * g + (j & 1)) & 7);
    uint32_t xrow = sb + OFF_X;

#pragma unroll 1
    for (int s = 0; s <= NB; ++s, acc += 32, xrow += 640) {
        uint32_t t0 = 0;
        if (s < NB) {
            stage_wo<0, 0>(WO, s & 1, acc, sb, w);
            t0 = clk32();
            TS(1, s * 16 + 0);
            const int ln = fresh_lane();
            poll_residual<0, false>(acc, 64.f, xrow, w, t0, b01, b2x);
            TS(1, s * 16 + 1);
            if (active) stage_mlp<0, 128>(W1, W2, cs1, b2x, s & 1, xrow, acc, sb, rsb, r, w, ln);
            t0 = clk32();
            TS(1, s * 16 + 2);
        }
        if (s >= 1) {
            stage_wo<1, -256>(WO, (s - 1) & 1, acc, sb, w);
            if (s == NB) t0 = clk32();
            TS(1, (s - 1) * 16 + 5);
        }
        if (s < NB) {
            const int ln = fresh_lane();
            const uint32_t xb = xrow + (ln & 4) * 80 + (ln & 3) * 16, qsb = (ln & 1) ? rsb : sb;
            poll_residual<128, true>(acc, (float)ACT_PAIRS, xrow, w, t0, b01, b2x);
            TS(1, s * 16 + 3);
            x_bar();
            float a[4] = {0.f, 0.f, 0.f, 0.f}, b[4] = {0.f, 0.f, 0.f, 0.f}, d[4] = {0.f, 0.f, 0.f, 0.f};
#pragma unroll
            for (int blk = 0; blk < 5; blk++) {
                uint4 B = lds128(xb + blk * 64);
                mma((2 * blk) % 3 == 0 ? a : (2 * blk) % 3 == 1 ? b : d, WQ[8 * blk], WQ[8 * blk + 1], WQ[8 * blk + 2], WQ[8 * blk + 3], B.x, B.y);
                mma((2 * blk + 1) % 3 == 0 ? a : (2 * blk + 1) % 3 == 1 ? b : d, WQ[8 * blk + 4], WQ[8 * blk + 5], WQ[8 * blk + 6], WQ[8 * blk + 7], B.z, B.w);
            }
            st_async_if((ln & 2) == 0, qsb + OFF_Q + (8 * w + (ln >> 2)) * 8 + r * 4,
                        __float_as_uint(((b[0] + b[3]) + (d[0] + d[3])) + (a[0] + a[3])), qsb + OFF_BAR + BAR_Q * 8);
            TS(1, s * 16 + 4);
        }
        if (s >= 1 && active) {
            const int ln = fresh_lane();
            poll_residual<-256, false>(acc, 64.f, xrow - 640, w, t0, b01, b2x);
            TS(1, (s - 1) * 16 + 6);
            stage_mlp<1, -128>(W1, W2, cs1, b2x, s & 1, xrow - 640, acc, sb, rsb, r, w, ln);
            TS(1, (s - 1) * 16 + 7);
        }
    }
}

__device__ __forceinline__ void moments_role(const Params& P, uint32_t sb, uint32_t rsb) {
    const int c = blockIdx.x, r = c & 1, p = c >> 1;
    const bool active = p < ACT_PAIRS, writer = !active && p < OUT_PAIR + 4;
#pragma unroll 1
    for (int i = 0; i < 3 * (NB + 2); i++) {
        const int s = i / 3, ph = i - 3 * s;
        const int lane = fresh_lane(), g = lane >> 2, j = lane & 3;
        if (ph == 2 && writer && s >= 2) {
            const int b = s - 2, vec = (p - OUT_PAIR) * 32 + lane, col = 40 * (vec >> 4) + 24 * (vec & 1) + ((vec >> 1) & 7);
            const uint4* acc = g_acc + (r * 16 + (vec >> 3)) * 256 + (vec & 7) + b * 32;
            const uint16_t* pb = reinterpret_cast<const uint16_t*>(P.b2) + 320 * r + col;
            const uint32_t xa = sb + OFF_X + b * 640 + col * 2;
            uint32_t x01 = lds16(xa) | (lds16(xa + 16) << 16), x2x = lds16(xa + 32), y01, y2x;
            const uint32_t b01 = (uint32_t)pb[0] | ((uint32_t)pb[8] << 16), b2x = pb[(vec & 1) ? 8 : 16];
            poll_sum<256>(acc, 64.f, y01, y2x);
            x01 = badd2(x01, y01); x2x = badd2(x2x, y2x);
            poll_sum<384>(acc, (float)ACT_PAIRS, y01, y2x);
            x01 = badd2(x01, badd2(y01, b01)); x2x = badd2(x2x, badd2(y2x, b2x));
            uint16_t* o = reinterpret_cast<uint16_t*>(P.out) + b * DM + 320 * r + col;
            o[0] = (uint16_t)x01;
            o[8] = (uint16_t)(x01 >> 16);
            if (!(vec & 1)) o[16] = (uint16_t)x2x;
            __syncwarp();
            TS(1, b * 16 + 8);
        }
        if (ph == 2 ? (s == 0 || s > NB || !active) : (s >= NB || (ph == 0 && !active))) continue;
        const uint32_t xb = sb + OFF_X + (g & 3) * 160 + j * 16 + (ph == 2 ? s - 1 : s) * 640;
        const uint32_t dst = (ph == 1 ? OFF_Q : ph == 0 ? OFF_H : OFF_H + 560) + 512;
        const uint32_t bar = OFF_BAR + (ph == 1 ? BAR_Q : ph == 0 ? BAR_H : BAR_H + 1) * 8;
        const uint32_t dsq = (g & 4) ? rsb : sb, dsu = (j & 2) ? rsb : sb;
        x_bar();
        uint4 B0 = lds128(xb), B1 = lds128(xb + 64);
        uint2 B2 = lds64(xb + 128 - j * 8);
        float a[4] = {0.f, 0.f, 0.f, 0.f}, b[4] = {0.f, 0.f, 0.f, 0.f};
        mma(a, B0.x, ONES, B0.y, ONES, B0.x, B0.y);
        mma(b, B0.z, ONES, B0.w, ONES, B0.z, B0.w);
        mma(a, B1.x, ONES, B1.y, ONES, B1.x, B1.y);
        mma(b, B1.z, ONES, B1.w, ONES, B1.z, B1.w);
        mma(a, B2.x, ONES, B2.y, ONES, B2.x, B2.y);
        st_async_if(j == ((g & 3) >> 1), dsq + dst + (r * 4 + (g & 3)) * 4, __float_as_uint((g & 1) ? a[1] + b[1] : a[0] + b[0]), dsq + bar);
        st_async_if(g == 0, dsu + dst + 32 + (r * 2 + (j & 1)) * 4, __float_as_uint((a[2] + b[2]) + (a[3] + b[3])), dsu + bar);
    }
}

struct Maps { CUtensorMap k, v, wq, wo, w1, w2; };

__device__ __forceinline__ void issue_weights(const Maps& M, int i, uint32_t sb, uint64_t pol) {
    const int c = blockIdx.x, r = c & 1, p = c >> 1;
    const uint32_t bar = sb + OFF_BAR + i * 8, dst = sb + i * SLOT;
    mbar_expect(bar, SLOT);
    if (i < 5) {
        tma2d(dst, &M.wq, 64 * p, 320 * r + 64 * i, bar, pol);
    } else if (i < 10) {
        tma2d(dst, &M.wo, 320 * r + 64 * (i - 5), 64 * p, bar, pol);
    } else {
        tma2d(dst, &M.w1, 32 * p, 320 * r + 64 * (i - 10), bar, pol);
        tma2d(dst + 4096, &M.w2, 320 * r + 64 * (i - 10), 32 * p, bar, pol);
    }
}

__device__ __forceinline__ void producer_role(const Maps& M, uint32_t sb) {
    const int c = blockIdx.x;
    const uint32_t bars = sb + OFF_BAR;
    uint64_t pol;
    asm("createpolicy.fractional.L2::evict_first.b64 %0, 1.0;" : "=l"(pol));
#pragma unroll 1
    for (int i = 0; i < NWI; i++) {
        if (i < WSTART) {
            mbar_init(bars + i * 8, 1);
            asm volatile("fence.mbarrier_init.release.cluster;" ::: "memory");
        } else {
            if (i == WSTART) asm volatile("st.volatile.shared.v2.u32 [%0], {%1, %2};" ::"r"(sb + OFF_PACE), "r"(0), "r"(WSTART) : "memory");
            if (i == WSTART) asm volatile("barrier.cluster.arrive.relaxed;\nbarrier.cluster.wait;" ::: "memory");
            mbar_wait(bars + (i - WSTART) * 8, 0);
        }
        issue_weights(M, i, sb, pol);
        TS(2, i);
    }
    const int x = (c & 2) * 32, y0 = (c >> 2) * SK + (SK - WIN) + (c & 1) * 512;
    uint32_t dst = sb + NWI * SLOT, bar = bars + NWI * 8, epar = 1;
    uint32_t wbar = bars + (NWI - WSTART) * 8, wpar = 0;
    int win = WSTART;
#pragma unroll 1
    for (int ii = 0; ii < NB * 16; ii++) {
        if (ii == TMP_SLOT - NWI) mbar_wait(bars + BAR_TMP * 8, 0);
        mbar_wait(bar + BAR_EMPTY * 8, epar);
        mbar_expect(bar, SLOT);
        const CUtensorMap* tm = (ii & 8) ? &M.v : &M.k;
        const int y = y0 + (ii >> 4) * (32 * SK) + (ii & 7) * 64;
        int target;
        asm volatile("ld.volatile.shared.u32 %0, [%1];" : "=r"(target) : "r"(sb + OFF_PACE + 4) : "memory");
        target = __shfl_sync(1u, target, 0);
        const int waits = target > win ? 0 : target < win ? 2 : 1;
        win += 1 - waits;
        if (waits == 2) {
            mbar_wait(wbar, wpar);
            wbar += 8; if (wbar == bars + NSLOT * 8) { wbar = bars; wpar ^= 1; }
        }
        if (waits) mbar_wait(wbar, wpar);
        tma2d(dst, tm, x, y, bar, pol);
        asm volatile("st.volatile.shared.u32 [%0], %1;" ::"r"(sb + OFF_PACE), "r"(ii + 1) : "memory");
        TS(2, ii + NWI);
        if (waits) { wbar += 8; if (wbar == bars + NSLOT * 8) { wbar = bars; wpar ^= 1; } }
        bar += 8; dst += SLOT;
        if (bar == bars + NSLOT * 8) { bar = bars; dst = sb; epar ^= 1; }
    }
}

__device__ __forceinline__ void cluster_sync() {
    asm volatile("barrier.cluster.arrive.relaxed.aligned;\nbarrier.cluster.wait.acquire.aligned;" ::: "memory");
}

__global__ void __cluster_dims__(2, 1, 1) __launch_bounds__(NTHREADS, 1)
fused_decode_kernel(const __grid_constant__ Maps M, const __grid_constant__ Params P) {
    extern __shared__ __align__(1024) unsigned char smem[];
    if (threadIdx.x == 0 && PRE_BYTES)
        asm volatile("cp.async.bulk.prefetch.L2.global [%0], %1;"
                     ::"l"(reinterpret_cast<const char*>(P.wq) + blockIdx.x * 40960), "r"(PRE_BYTES) : "memory");
    if (threadIdx.x == 32) asm volatile("prefetch.tensormap [%0];" ::"l"(&M.wq) : "memory");
    const uint32_t sb = (uint32_t)__cvta_generic_to_shared(smem);
    const int lane = threadIdx.x & 31, c = blockIdx.x;
    const int warp = __shfl_sync(0xffffffffu, threadIdx.x >> 5, 0);
    const uint32_t bars = sb + OFF_BAR;
    uint32_t rsb;
    asm("mapa.shared::cluster.u32 %0, %1, %2;" : "=r"(rsb) : "r"(sb), "r"((c & 1) ^ 1));
    if (warp < 12) {
        if (lane == 0) {
            if (sb & 1023) __trap();
#pragma unroll 1
            for (int b = WSTART + warp; b <= BAR_INIT; b += 12) {
                mbar_init(bars + b * 8, b < BAR_EMPTY ? 1 : b < BAR_O ? 4 : (b == BAR_TMP || b == BAR_Q1) ? 8 : 1);
                if (b >= BAR_O && b <= BAR_P)
                    mbar_expect(bars + b * 8, b < BAR_H ? TX_O : b == BAR_H ? TX_H : b == BAR_H + 1 ? 512u : b == BAR_Q ? TX_Q : TX_P);
            }
            asm volatile("fence.mbarrier_init.release.cluster;" ::: "memory");
        }
        __syncwarp();
        cluster_sync();
        asm volatile("setmaxnreg.inc.sync.aligned.u32 %0;" ::"n"(REG_WORK));
        if (warp < 4) attention_role(sb, rsb, warp, lane, P.zero);
        else chain_role(P, sb, rsb, warp - 4, lane);
    } else {
        asm volatile("setmaxnreg.dec.sync.aligned.u32 %0;" ::"n"(REG_MISC));
        if (warp == 13) {
            cluster_sync();
            moments_role(P, sb, rsb);
        } else if (warp == 14) {
            cluster_sync();
            TS(2, 200);
#pragma unroll 1
            for (int i = 0; i < 16; i++) g_xch[c * 512 + i * 32 + lane] = make_uint4(0, 0, 0, 0);
            g_acc[c * 64 + lane] = make_uint4(0, 0, 0, 0);
            g_acc[c * 64 + 32 + lane] = make_uint4(0, 0, 0, 0);
            __syncwarp();
            if (lane == 0) {
                unsigned seen;
                asm volatile("atom.acq_rel.gpu.global.add.u32 %0, [%1], 1;" : "=r"(seen) : "l"(&g_arrive) : "memory");
                TS(2, 201);
                const unsigned target = (seen / NCTA + 1) * NCTA;
                int n = 0;
                do {
                    __nanosleep(200);
                    asm volatile("ld.acquire.gpu.global.u32 %0, [%1];" : "=r"(seen) : "l"(&g_arrive) : "memory");
                    spin_guard(n);
                } while ((int)(seen - target) < 0);
                mbar_arrive(bars + BAR_INIT * 8);
                TS(2, 202);
            }
        } else if (warp == 15) {
            asm volatile("barrier.cluster.arrive.relaxed.aligned;" ::: "memory");
            if (lane == 0) {
                asm volatile("prefetch.tensormap [%0];\nprefetch.tensormap [%1];\nprefetch.tensormap [%2];\n"
                             "prefetch.tensormap [%3];\nprefetch.tensormap [%4];"
                             ::"l"(&M.wo), "l"(&M.w1), "l"(&M.w2), "l"(&M.k), "l"(&M.v) : "memory");
            }
            if (lane < 2) {
                const char* base = reinterpret_cast<const char*>(lane ? P.v : P.k);
                asm volatile("prefetch.global.L2 [%0];" ::"l"(base + ((size_t)(c >> 2) * SK + (SK - WIN) + (c & 1) * 512) * 256 + (c & 2) * 64) : "memory");
            }
            __syncwarp();
            asm volatile("barrier.cluster.wait.aligned;" ::: "memory");
            if (lane == 0) {
                int mine, told = 0, n = 0;
                do {
                    __nanosleep(PACE_GAP);
                    asm volatile("ld.volatile.shared.u32 %0, [%1];" : "=r"(mine) : "r"(sb + OFF_PACE) : "memory");
                    if (mine) {
                        unsigned all;
                        asm volatile("atom.relaxed.gpu.global.add.u32 %0, [%1], %2;" : "=r"(all) : "l"(&g_progress), "r"(mine - told) : "memory");
                        told = mine;
                        const int lag = (int)(all & (128 * NCTA - 1)) - mine * NCTA + LEAD_BIAS;
                        const int win = min(max(WINDOW + (lag + 64 * LEAD_STEP) / LEAD_STEP - 64, WMIN), WMAX);
                        if (mine >= WSHRINK) asm volatile("st.volatile.shared.u32 [%0], %1;" ::"r"(sb + OFF_PACE + 4), "r"(win) : "memory");
                    }
                    spin_guard(n);
                } while (mine < NB * 16);
            }
        } else {
            if (lane == 0) {
                producer_role(M, sb);
            }
        }
    }
}

typedef CUresult (*EncodeFn)(CUtensorMap*, CUtensorMapDataType, cuuint32_t, void*, const cuuint64_t*, const cuuint64_t*,
                             const cuuint32_t*, const cuuint32_t*, CUtensorMapInterleave, CUtensorMapSwizzle,
                             CUtensorMapL2promotion, CUtensorMapFloatOOBfill);

bool make_map(EncodeFn enc, CUtensorMap* m, const void* base, uint64_t cols, uint64_t rows, uint32_t bx, uint32_t by, bool swz) {
    cuuint64_t gd[2] = {cols, rows}, gs[1] = {cols * 2};
    cuuint32_t box[2] = {bx, by}, es[2] = {1, 1};
    return enc(m, CU_TENSOR_MAP_DATA_TYPE_BFLOAT16, 2, const_cast<void*>(base), gd, gs, box, es, CU_TENSOR_MAP_INTERLEAVE_NONE,
               swz ? CU_TENSOR_MAP_SWIZZLE_128B : CU_TENSOR_MAP_SWIZZLE_NONE, CU_TENSOR_MAP_L2_PROMOTION_L2_128B,
               CU_TENSOR_MAP_FLOAT_OOB_FILL_NONE) == CUDA_SUCCESS;
}

}

extern "C" void kernel_launch(void* const* d_in, const int* in_sizes, int n_in, void* d_out, int out_size) {
    (void)in_sizes; (void)n_in; (void)out_size;
    void* fn = nullptr;
    cudaDriverEntryPointQueryResult qr;
    if (cudaGetDriverEntryPoint("cuTensorMapEncodeTiled", &fn, cudaEnableDefault, &qr) != cudaSuccess || !fn) return;
    EncodeFn enc = (EncodeFn)fn;
    Maps M;
    bool ok = make_map(enc, &M.k, d_in[1], 128, (uint64_t)NB * 32 * SK, 64, 64, true) &&
              make_map(enc, &M.v, d_in[2], 128, (uint64_t)NB * 32 * SK, 64, 64, true) &&
              make_map(enc, &M.wq, d_in[3], 4096, DM, 64, 64, true) &&
              make_map(enc, &M.wo, d_in[4], DM, 4096, 64, 64, true) &&
              make_map(enc, &M.w1, d_in[6], FF, DM, 32, 64, false) &&
              make_map(enc, &M.w2, d_in[8], DM, FF, 64, 32, true);
    cudaFuncAttributes fa;
    ok = ok && cudaFuncGetAttributes(&fa, fused_decode_kernel) == cudaSuccess &&
         fa.numRegs * 4 >= 3 * REG_WORK + REG_MISC;
    if (!ok) return;
    cudaFuncSetAttribute(fused_decode_kernel, cudaFuncAttributeMaxDynamicSharedMemorySize, SMEM_BYTES);
    Params P;
    P.x = (const __nv_bfloat16*)d_in[0];
    P.wq = (const __nv_bfloat16*)d_in[3];
    P.wo = (const __nv_bfloat16*)d_in[4];
    P.k = (const __nv_bfloat16*)d_in[1];
    P.v = (const __nv_bfloat16*)d_in[2];
    P.b1 = (const __nv_bfloat16*)d_in[7];
    P.b2 = (const __nv_bfloat16*)d_in[9];
    P.out = (__nv_bfloat16*)d_out;
    P.zero = 0;
    fused_decode_kernel<<<NCTA, NTHREADS, SMEM_BYTES>>>(M, P);
}
```

```cpp
#include <cuda_runtime.h>
#include <cuda_bf16.h>
#include <cuda.h>
#include <stdint.h>

namespace {

constexpr int NB = 8, DM = 640, SK = 4096, WIN = 1024, FF = 1728;
constexpr int NCTA = 128, NTHREADS = 512;
constexpr int SLOT = 8192, NSLOT = 27, NWI = 15;
constexpr int ACT_PAIRS = FF / 32;
constexpr int OUT_PAIR = ACT_PAIRS;
#define HOLD 5
#define WINDOW 4
#define POLL_DELAY 400
#define XCH1_DELAY 1400
#define WSTART 6
#define WSHRINK 3
#define NTOP 6
#define PRE_BYTES 16384
#define LEAD_STEP 224
#define WMAX 6
#define LEAD_BIAS 155
#define PACE_GAP 50
#define END_FREE 0
#define XCH2_DELAY 280
#define GRP 8
#define LINE 1024
#define HOP 32768
#define POST_DELAY 350
#define LOOK_V 0
#define WATCHDOG 2000000000LL
#define WAITV 1
#define DOGV 1
#define PRE_DELAY 0
#define WGAP 40
#define PRE_IN 3
#define XZERO 16
#define XCH_AT 3
constexpr int REG_WORK = 160, REG_MISC = 32;

constexpr int OFF_BAR = NSLOT * SLOT;
constexpr int BAR_EMPTY = NSLOT, BAR_O = 2 * NSLOT, BAR_M = BAR_O + 2, BAR_H = BAR_M + 1, BAR_Q = BAR_H + 2,
              BAR_P = BAR_Q + 1, BAR_Q1 = BAR_P + 1, BAR_INIT = BAR_Q1 + 1, BAR_DONE = BAR_INIT + 1,
              BAR_END = BAR_DONE + 1,
              BAR_WIN = BAR_END + 1;
constexpr int OFF_SINK = OFF_BAR + 576;
constexpr int OFF_O = OFF_BAR + 640;
constexpr int OFF_ML = OFF_O + 2 * 1024;
constexpr int OFF_H = OFF_ML + 128, H_SZ = 576;
constexpr int OFF_Q = OFF_H + 2 * H_SZ;
constexpr int OFF_Q1 = OFF_Q + H_SZ;
constexpr int OFF_CSQ = OFF_Q1 + 1024;
constexpr int OFF_X = OFF_CSQ + 256;
constexpr int SMEM_BYTES = OFF_X + NB * 640 + 32;
static_assert(SMEM_BYTES <= 232448, "smem");
static_assert(BAR_WIN + 1 < 72, "barriers");
constexpr uint32_t TX_O = 8 * 128, TX_M = 8 * 64, TX_H = 2 * (256 + 24), TX_Q = 2 * (256 + 24), TX_P = 9 * 64 * 4;
static_assert(TX_P <= OFF_H + H_SZ - OFF_O, "prologue exchange lives in the O buffers");

constexpr float LN_EPS = 1e-5f;
constexpr float LOG2E = 1.4426950408889634f;
constexpr float SCALE = 0.08838834764831845f;
constexpr uint32_t ONES = 0x3F803F80u;

__device__ __forceinline__ int acc_index(int v) { return (v / GRP) * (LINE / 16) + v % GRP; }
constexpr int ACC_BYTES = (256 / GRP - 1) * LINE + 31 * HOP + GRP * 16;

__device__ __align__(4096) uint4 g_acc[ACC_BYTES / 16];
__device__ uint4 g_xch[NCTA * 4 * 128];
__device__ unsigned g_progress;
__device__ unsigned g_arrive;
#define TS(role, idx) do {} while (0)
#define TQ(cond, idx) do {} while (0)
#define TQ_FLUSH() do {} while (0)
#define TT(cond, idx) do {} while (0)

__device__ __forceinline__ uint32_t clk32() { uint32_t c; asm volatile("mov.u32 %0, %%clock;" : "=r"(c)); return c; }
__device__ __forceinline__ void mbar_init(uint32_t bar, uint32_t cnt) {
    asm volatile("mbarrier.init.shared::cta.b64 [%0], %1;" ::"r"(bar), "r"(cnt) : "memory");
}
__device__ __forceinline__ void mbar_expect(uint32_t bar, uint32_t bytes) {
    asm volatile("mbarrier.arrive.expect_tx.shared::cta.b64 _, [%0], %1;" ::"r"(bar), "r"(bytes) : "memory");
}
__device__ __forceinline__ void mbar_arrive(uint32_t bar) {
    asm volatile("mbarrier.arrive.shared::cta.b64 _, [%0];" ::"r"(bar) : "memory");
}
__device__ __forceinline__ void mbar_expect_if(bool on, uint32_t bar, uint32_t bytes) {
    asm volatile("{\n.reg .pred p;\nsetp.ne.u32 p, %2, 0;\n@p mbarrier.arrive.expect_tx.shared::cta.b64 _, [%0], %1;\n}"
                 ::"r"(bar), "r"(bytes), "r"((uint32_t)on) : "memory");
}
__device__ __forceinline__ void mbar_arrive_if(bool on, uint32_t bar) {
    asm volatile("{\n.reg .pred p;\nsetp.ne.u32 p, %1, 0;\n@p mbarrier.arrive.shared::cta.b64 _, [%0];\n}" ::"r"(bar), "r"((uint32_t)on) : "memory");
}
__device__ __forceinline__ bool mbar_test(uint32_t bar, uint32_t parity) {
    uint32_t ok;
    asm volatile("{\n.reg .pred p;\nmbarrier.test_wait.parity.shared::cta.b64 p, [%1], %2;\nselp.u32 %0, 1, 0, p;\n}"
                 : "=r"(ok) : "r"(bar), "r"(parity) : "memory");
    return ok;
}
__device__ __forceinline__ void mbar_wait(uint32_t bar, uint32_t parity) {
    asm volatile("{\n.reg .pred p;\nW_%=:\nmbarrier.try_wait.parity.shared::cta.b64 p, [%0], %1;\n@!p pmevent 0;\n@!p bra.uni W_%=;\n}\n"
                 ::"r"(bar), "r"(parity) : "memory");
}
__device__ __forceinline__ void st_async(uint32_t addr, uint32_t v, uint32_t bar) {
    asm volatile("st.async.shared::cluster.mbarrier::complete_tx::bytes.b32 [%0], %1, [%2];" ::"r"(addr), "r"(v), "r"(bar) : "memory");
}
__device__ __forceinline__ void st_async_if(bool on, uint32_t addr, uint32_t v, uint32_t bar) {
    asm volatile("{\n.reg .pred p;\nsetp.ne.u32 p, %3, 0;\n@p st.async.shared::cluster.mbarrier::complete_tx::bytes.b32 [%0], %1, [%2];\n}"
                 ::"r"(addr), "r"(v), "r"(bar), "r"((uint32_t)on) : "memory");
}
__device__ __forceinline__ void tma2d(uint32_t dst, const CUtensorMap* tm, int x, int y, uint32_t bar, uint64_t pol) {
    asm volatile("cp.async.bulk.tensor.2d.shared::cluster.global.mbarrier::complete_tx::bytes.L2::cache_hint [%0], [%1, {%3, %4}], [%2], %5;"
                 ::"r"(dst), "l"(tm), "r"(bar), "r"(x), "r"(y), "l"(pol) : "memory");
}
__device__ __forceinline__ bool elect_one() {
    uint32_t e;
    asm volatile("{\n.reg .pred p;\nelect.sync _|p, 0xffffffff;\nselp.u32 %0, 1, 0, p;\n}" : "=r"(e));
    return e;
}
__device__ __forceinline__ void ldsm4(uint32_t& r0, uint32_t& r1, uint32_t& r2, uint32_t& r3, uint32_t a) {
    asm volatile("ldmatrix.sync.aligned.m8n8.x4.shared.b16 {%0,%1,%2,%3}, [%4];" : "=r"(r0), "=r"(r1), "=r"(r2), "=r"(r3) : "r"(a));
}
__device__ __forceinline__ void ldsm4t(uint32_t& r0, uint32_t& r1, uint32_t& r2, uint32_t& r3, uint32_t a) {
    asm volatile("ldmatrix.sync.aligned.m8n8.x4.trans.shared.b16 {%0,%1,%2,%3}, [%4];" : "=r"(r0), "=r"(r1), "=r"(r2), "=r"(r3) : "r"(a));
}
__device__ __forceinline__ void mma(float (&c)[4], uint32_t a0, uint32_t a1, uint32_t a2, uint32_t a3, uint32_t b0, uint32_t b1) {
    asm("mma.sync.aligned.m16n8k16.row.col.f32.bf16.bf16.f32 {%0,%1,%2,%3}, {%4,%5,%6,%7}, {%8,%9}, {%0,%1,%2,%3};"
        : "+f"(c[0]), "+f"(c[1]), "+f"(c[2]), "+f"(c[3]) : "r"(a0), "r"(a1), "r"(a2), "r"(a3), "r"(b0), "r"(b1));
}
__device__ __forceinline__ uint4 lds128(uint32_t a) {
    uint4 v; asm volatile("ld.shared.v4.b32 {%0,%1,%2,%3}, [%4];" : "=r"(v.x), "=r"(v.y), "=r"(v.z), "=r"(v.w) : "r"(a)); return v;
}
__device__ __forceinline__ uint4 lds128_if(bool on, uint32_t a) {
    uint4 v;
    asm volatile("{\n.reg .pred p;\nsetp.ne.u32 p, %5, 0;\nmov.b32 %0, 0;\nmov.b32 %1, 0;\nmov.b32 %2, 0;\nmov.b32 %3, 0;\n"
                 "@p ld.shared.v4.b32 {%0,%1,%2,%3}, [%4];\n}" : "=r"(v.x), "=r"(v.y), "=r"(v.z), "=r"(v.w) : "r"(a), "r"((uint32_t)on));
    return v;
}
__device__ __forceinline__ uint2 lds64_if(bool on, uint32_t a) {
    uint2 v;
    asm volatile("{\n.reg .pred p;\nsetp.ne.u32 p, %3, 0;\nmov.b32 %0, 0;\nmov.b32 %1, 0;\n"
                 "@p ld.shared.v2.b32 {%0,%1}, [%2];\n}" : "=r"(v.x), "=r"(v.y) : "r"(a), "r"((uint32_t)on));
    return v;
}
__device__ __forceinline__ float4 lds128f(uint32_t a) {
    float4 v; asm volatile("ld.shared.v4.f32 {%0,%1,%2,%3}, [%4];" : "=f"(v.x), "=f"(v.y), "=f"(v.z), "=f"(v.w) : "r"(a)); return v;
}
__device__ __forceinline__ float2 lds64f(uint32_t a) {
    float2 v; asm volatile("ld.shared.v2.f32 {%0,%1}, [%2];" : "=f"(v.x), "=f"(v.y) : "r"(a)); return v;
}
__device__ __forceinline__ float lds32f(uint32_t a) { float v; asm volatile("ld.shared.f32 %0, [%1];" : "=f"(v) : "r"(a)); return v; }
__device__ __forceinline__ void cluster_wait() { asm volatile("barrier.cluster.wait.aligned;" ::: "memory"); }
__device__ __forceinline__ void sts32(uint32_t a, uint32_t v) { asm volatile("st.shared.b32 [%0], %1;" ::"r"(a), "r"(v) : "memory"); }
__device__ __forceinline__ uint32_t pack2(float lo, float hi) {
    uint32_t d; asm("cvt.rn.bf16x2.f32 %0, %1, %2;" : "=r"(d) : "f"(hi), "f"(lo)); return d;
}
__device__ __forceinline__ float rbf(float x) { return __uint_as_float(pack2(x, 0.f) << 16); }
__device__ __forceinline__ float ex2(float x) { float y; asm("ex2.approx.ftz.f32 %0, %1;" : "=f"(y) : "f"(x)); return y; }
__device__ __forceinline__ float fsqrt(float x) { float y; asm("sqrt.approx.f32 %0, %1;" : "=f"(y) : "f"(x)); return y; }
__device__ __forceinline__ float fdiv(float a, float b) { float y; asm("div.full.f32 %0, %1, %2;" : "=f"(y) : "f"(a), "f"(b)); return y; }
__device__ __forceinline__ float warp_max(float x) {
    int i = __float_as_int(x), m;
    i ^= (i >> 31) & 0x7fffffff;
    asm volatile("redux.sync.max.s32 %0, %1, 0xffffffff;" : "=r"(m) : "r"(i));
    m ^= (m >> 31) & 0x7fffffff;
    return __int_as_float(m);
}
__device__ __forceinline__ float warp_sum(float x) {
#pragma unroll
    for (int o = 16; o; o >>= 1) x += __shfl_xor_sync(0xffffffffu, x, o);
    return x;
}
__device__ __forceinline__ uint4 ld_relaxed(const uint4* p) {
    uint4 v; asm volatile("ld.relaxed.gpu.global.v4.b32 {%0,%1,%2,%3}, [%4];" : "=r"(v.x), "=r"(v.y), "=r"(v.z), "=r"(v.w) : "l"(p) : "memory");
    return v;
}
__device__ __forceinline__ float rcp(float x) { float y; asm("rcp.approx.ftz.f32 %0, %1;" : "=f"(y) : "f"(x)); return y; }
__device__ __forceinline__ float rsq(float x) { float y; asm("rsqrt.approx.ftz.f32 %0, %1;" : "=f"(y) : "f"(x)); return y; }
__device__ __forceinline__ int fresh_lane() { int l; asm volatile("mov.u32 %0, %%laneid;" : "=r"(l)); return l; }
__device__ __forceinline__ uint32_t badd2(uint32_t a, uint32_t b) { uint32_t d; asm("add.rn.bf16x2 %0, %1, %2;" : "=r"(d) : "r"(a), "r"(b)); return d; }
__device__ __forceinline__ uint32_t lds16(uint32_t a) { uint32_t v; asm volatile("ld.shared.u16 %0, [%1];" : "=r"(v) : "r"(a)); return v; }
__device__ __forceinline__ void sign_off(uint32_t sb) { mbar_arrive_if(fresh_lane() == 0, sb + OFF_BAR + BAR_DONE * 8); }

struct Params {
    const __nv_bfloat16* x;
    const __nv_bfloat16* wq;
    const __nv_bfloat16* b1;
    const __nv_bfloat16* b2;
    __nv_bfloat16* out;
    uint32_t zero;
};

__device__ __forceinline__ void xch_send(uint32_t (&s)[4], uint4* dst, uint32_t tag) {
#pragma unroll
    for (int i = 0; i < 4; i++) s[i] = (s[i] & ~1u) | tag;
    asm volatile("st.relaxed.gpu.global.v4.b32 [%0], {%1,%2,%3,%4};" ::"l"(dst), "r"(s[0]), "r"(s[1]), "r"(s[2]), "r"(s[3]) : "memory");
}

__device__ __forceinline__ void xch_recv(uint4& v, const uint4* src, uint32_t tag) {
    while (__any_sync(0xffffffffu, (((v.x ^ tag) | (v.y ^ tag)) | ((v.z ^ tag) | (v.w ^ tag))) & 1u)) v = ld_relaxed(src);
}
template <bool ROUND>
__device__ __forceinline__ void softmax4(uint32_t (&s)[4], const uint4& v) {
    float t[4] = {__uint_as_float(s[0]) + __uint_as_float(v.x), __uint_as_float(s[1]) + __uint_as_float(v.y),
                  __uint_as_float(s[2]) + __uint_as_float(v.z), __uint_as_float(s[3]) + __uint_as_float(v.w)};
    if (ROUND) {
#pragma unroll
        for (int i = 0; i < 4; i++) t[i] = rbf(rbf(t[i]) * SCALE);
    }
    constexpr float C = ROUND ? LOG2E : SCALE * LOG2E;
    const float m = warp_max(fmaxf(fmaxf(t[0], t[1]), fmaxf(t[2], t[3]))) * C;
#pragma unroll
    for (int i = 0; i < 4; i++) t[i] = ex2(fmaf(t[i], C, -m));
    s[0] = pack2(t[0], t[1]);
    s[1] = pack2(t[2], t[3]);
    s[2] = __float_as_uint(m);
    uint32_t l;
    asm volatile("redux.sync.add.u32 %0, %1, 0xffffffff;" : "=r"(l) : "r"(__float2uint_rn(((t[0] + t[1]) + (t[2] + t[3])) * 16777216.f)));
    s[3] = __float_as_uint(__uint2float_rn(l));
}

__device__ __forceinline__ void publish_ml(const uint32_t (&s)[4], int k, uint32_t sb, uint32_t rsb, int src, int lane) {
    const uint32_t base = (lane & 16) ? sb : rsb, i = lane & 15;
    st_async(base + i * 4 + (i < 2 ? OFF_ML + k * 64 + src * 8 : OFF_SINK), (lane & 1) ? s[3] : s[2], base + OFF_BAR + (k ? BAR_O + 1 : BAR_M) * 8);
}
__device__ __forceinline__ void publish_o(const float (&o)[4][4], int k, uint32_t sb, uint32_t rsb, int src, int lane) {
    const int g = lane >> 2, j = lane & 3;
    const float lo = (j & 2) ? ((j & 1) ? o[3][0] : o[2][0]) : ((j & 1) ? o[1][0] : o[0][0]);
    const float hi = (j & 2) ? ((j & 1) ? o[3][2] : o[2][2]) : ((j & 1) ? o[1][2] : o[0][2]);
    const uint32_t wd = pack2(lo, hi);
    const uint32_t off = OFF_O + k * 1024 + src * 128 + (8 * j + (((g - 2 * j) ^ (src << 2)) & 7)) * 4, bar = OFF_BAR + (BAR_O + k) * 8;
    st_async(rsb + off, wd, rsb + bar);
    st_async(sb + off, wd, sb + bar);
}

__device__ __forceinline__ uint32_t next_slot(uint32_t sl) { return sl == NSLOT - 1 ? 0 : sl + 1; }
template <int N>
__device__ __forceinline__ uint32_t release_slots(uint32_t bars, uint32_t sl, int lane, const uint32_t* frag, uint32_t zero) {
    uint32_t dep = 0;
#pragma unroll
    for (int i = 0; i < 4 * N; i++) dep |= frag[4 * i];
    uint32_t t = sl + lane;
    if (t >= NSLOT) t -= NSLOT;
    mbar_arrive_if(lane < N, bars + (BAR_EMPTY + t) * 8 + (dep & zero));
    return sl + N >= NSLOT ? sl + N - NSLOT : sl + N;
}

#define TQW 0
__device__ __forceinline__ void attention_role(uint32_t sb, uint32_t rsb, int w, int lane0, uint32_t zero) {
    const int c = blockIdx.x, r = c & 1;
    const int mi = lane0 >> 3, i8 = lane0 & 7;
    const uint32_t bars = sb + OFF_BAR;
    uint32_t koff, voff;
    {
        int row = 16 * w + ((mi & 1) ? 8 + ((i8 + 4) & 7) : i8);
        koff = sb + row * 128 + (((mi >> 1) ^ (row & 7)) << 4);
        int gi = (i8 >> 1) + 4 * (mi >> 1);
        row = 16 * w + ((i8 & 1) ? 8 + ((gi + 4) & 7) : gi);
        voff = sb + row * 128 + (((mi & 1) ^ (row & 7)) << 4);
    }
    uint4* const xin = g_xch + c * 512 + w * 32 + lane0;
    const int xo = (c & 2) ? -1024 : 1024;
    uint32_t hold[HOLD * 16];
#pragma unroll
    for (int i = 0; i < HOLD * 16; i++) hold[i] = 0;

    cluster_wait();
    mbar_wait(bars + BAR_Q1 * 8, 0);

    uint32_t ksl = NWI, kpar = 0;
    uint32_t psl = 0;
#pragma unroll 1
    for (int s = -1;; ++s) {
        const int n = s + 1;
        const uint32_t tag1 = ((n >> 1) & 1) ^ 1, tag2 = ((s >> 1) & 1) ^ 1;
        uint32_t sl = ksl, par = kpar, s1[4] = {0, 0, 0, 0};
        if (n < NB) {
            const int lane = fresh_lane(), j = lane & 3;
            uint4 qa = lds128(sb + OFF_Q1 + n * 128 + j * 32), qb = lds128(sb + OFF_Q1 + n * 128 + j * 32 + 16);
#pragma unroll 1
            for (int cp = 0; cp < 4; cp++) {
                uint32_t base[2];
#pragma unroll
                for (int h = 0; h < 2; h++) {
                    mbar_wait(bars + sl * 8, par);
                    base[h] = koff + sl * SLOT;
                    if (++sl == NSLOT) { sl = 0; par ^= 1; }
                }
#pragma unroll
                for (int h = 0; h < 2; h++) {
                    uint32_t a[16];
                    float acc[4] = {0.f, 0.f, 0.f, 0.f}, acd[4] = {0.f, 0.f, 0.f, 0.f};
#pragma unroll
                    for (int ks = 0; ks < 4; ks++) ldsm4(a[4 * ks], a[4 * ks + 1], a[4 * ks + 2], a[4 * ks + 3], base[h] ^ (ks << 5));
                    mma(acc, a[0], a[1], a[2], a[3], qa.x, qa.y);
                    mma(acd, a[4], a[5], a[6], a[7], qa.z, qa.w);
                    mma(acc, a[8], a[9], a[10], a[11], qb.x, qb.y);
                    mma(acd, a[12], a[13], a[14], a[15], qb.z, qb.w);
                    if (j == cp) { s1[2 * h] = __float_as_uint(acc[0] + acd[0]); s1[2 * h + 1] = __float_as_uint(acc[2] + acd[2]); }
                }
            }
            if (n == 0) mbar_wait(bars + BAR_INIT * 8, 0);
            xch_send(s1, xin + (xo + (n & 1) * 128), tag1);
            TS(0, n * 16 + 0);
        }
        uint32_t s2[4], here = 0;
        uint4 v2;
        if (s >= 0) {
            const int lane = fresh_lane(), j = lane & 3;
            const uint32_t t0 = clk32();
            uint32_t a[(8 - HOLD) * 16], qf[8];
            float rs;
            uint32_t t = psl;
#pragma unroll
            for (int i = 0; i < 8 - HOLD; i++) {
#pragma unroll
                for (int ks = 0; ks < 4; ks++) {
                    const int q = i * 16 + ks * 4;
                    ldsm4(a[q], a[q + 1], a[q + 2], a[q + 3], (koff + t * SLOT) ^ (ks << 5));
                }
                t = next_slot(t);
            }
            psl = release_slots<8 - HOLD>(bars, psl, lane, a, zero);
            const uint32_t qa = sb + OFF_Q + lane * 8;
            const float2 cs = lds64f(qa + (OFF_CSQ - OFF_Q));
            while (clk32() - t0 < XCH1_DELAY && !mbar_test(bars + BAR_Q * 8, s & 1)) {}
            uint4 v1 = ld_relaxed(xin + (n & 1) * 128);
            mbar_wait(bars + BAR_Q * 8, s & 1);
            TS(0, s * 16 + 4); TQ(s == 7, 1);
            {
                const float4 su = lds128f(sb + OFF_Q + 544);
                const float2 pq = lds64f(qa), pr = lds64f(qa + 256);
                mbar_expect_if(w + lane == 0, bars + BAR_Q * 8, TX_Q);
                const float mean = ((su.x + su.y) + (su.z + su.w)) * (1.f / DM);
                const uint32_t pk = pack2(pq.x + pr.x - mean * cs.x, pq.y + pr.y - mean * cs.y);
#pragma unroll
                for (int i = 0; i < 8; i++) qf[i] = i ? __shfl_xor_sync(0xffffffffu, pk, 4 * i) : pk;
                const uint32_t va = sb + OFF_Q + 512 + (qf[3] & zero);
                const float4 sa = lds128f(va), sc = lds128f(va + 16);
                rs = rsq(fmaxf((((sa.x + sa.y) + (sa.z + sa.w)) + ((sc.x + sc.y) + (sc.z + sc.w))) * (1.f / DM) - mean * mean, 0.f) + LN_EPS);
            }
#pragma unroll
            for (int ch = 0; ch < 8; ch++) {
                const int qx = ch >> 1;
                const uint32_t* kf = ch < HOLD ? hold + ch * 16 : a + (ch - HOLD) * 16;
                float acc[4] = {0.f, 0.f, 0.f, 0.f};
#pragma unroll
                for (int i = 0; i < 4; i++) {
                    const int ks = i ^ qx;
                    mma(acc, kf[4 * ks], kf[4 * ks + 1], kf[4 * ks + 2], kf[4 * ks + 3], qf[2 * i], qf[2 * i + 1]);
                }
                if (ch < 2 || j == qx) { s2[(ch & 1) * 2] = __float_as_uint(acc[0]); s2[(ch & 1) * 2 + 1] = __float_as_uint(acc[2]); }
            }
#pragma unroll
            for (int i = 0; i < 4; i++) s2[i] = __float_as_uint(__uint_as_float(s2[i]) * rs);
            xch_send(s2, xin + (xo + (2 + (s & 1)) * 128), tag2);
            TS(0, s * 16 + 5); TQ(s == 7, 2);
            const uint32_t t1 = clk32();
            t = psl;
#pragma unroll
            for (int i = 0; i < HOLD; i++) {
                const uint32_t base = voff + t * SLOT;
#pragma unroll
                for (int mt = 0; mt < 4; mt++) {
                    const int q = i * 16 + mt * 4;
                    ldsm4t(hold[q], hold[q + 1], hold[q + 2], hold[q + 3], base ^ (mt << 5));
                }
                t = next_slot(t);
                if (i == XCH_AT) {
                    if (n < NB) {
                        release_slots<2>(bars, psl, lane, hold, zero);
                        asm volatile("{\n.reg .pred p, q;\nsetp.lt.u32 p, %3, 8;\nsetp.ne.u32 q, 0, 0;\n"
                                     "@p mbarrier.test_wait.parity.shared::cta.b64 q, [%1], %2;\nselp.u32 %0, 1, 0, q;\n}"
                                     : "=r"(here) : "r"(bars + (sl + lane >= NSLOT ? sl + lane - NSLOT : sl + lane) * 8),
                                       "r"(sl + lane >= NSLOT ? par ^ 1 : par), "r"(lane) : "memory");
                        xch_recv(v1, xin + (n & 1) * 128, tag1);
                        softmax4<true>(s1, v1);
                    }
                    while (clk32() - t1 < XCH2_DELAY) {}
                    v2 = ld_relaxed(xin + (2 + (s & 1)) * 128);
                }
            }
            TS(0, s * 16 + 6);
        } else {
            __nanosleep(600);
            uint4 v1 = ld_relaxed(xin);
            xch_recv(v1, xin, tag1);
            softmax4<true>(s1, v1);
            s2[0] = s2[1] = s2[2] = s2[3] = 0;
            v2 = make_uint4(0, 0, 0, 0);
        }
        float o[4][4];
        if (n < NB) {
            const int lane = fresh_lane(), j4 = (lane & 3) * 4;
            const uint32_t got = __ballot_sync(0xffffffffu, here);
            uint32_t f[2][16], pb[2][2];
            publish_ml(s1, 0, sb, rsb, 4 * r + w, lane);
#pragma unroll
            for (int mt = 0; mt < 4; mt++) o[mt][0] = o[mt][1] = o[mt][2] = o[mt][3] = 0.f;
#pragma unroll
            for (int u = 0; u <= 8; u++) {
                if (u < 8) {
                    const uint32_t base = voff + sl * SLOT;
                    pb[u & 1][0] = __shfl_sync(0xffffffffu, s1[u & 1], j4 + (u >> 1));
                    pb[u & 1][1] = __shfl_sync(0xffffffffu, s1[u & 1], j4 + 16 + (u >> 1));
                    if (!((got >> u) & 1)) mbar_wait(bars + sl * 8, par);
#pragma unroll
                    for (int mt = 0; mt < 4; mt++) ldsm4t(f[u & 1][4 * mt], f[u & 1][4 * mt + 1], f[u & 1][4 * mt + 2], f[u & 1][4 * mt + 3], base ^ (mt << 5));
                    if (++sl == NSLOT) { sl = 0; par ^= 1; }
                }
                if (u == 0) release_slots<HOLD - 2>(bars, psl + 2, s >= 0 ? lane : 32, hold + 32, zero);
                if (u > 0) {
                    const uint32_t* vf = f[(u - 1) & 1];
#pragma unroll
                    for (int mt = 0; mt < 4; mt++) mma(o[mt], vf[4 * mt], vf[4 * mt + 1], vf[4 * mt + 2], vf[4 * mt + 3], pb[(u - 1) & 1][0], pb[(u - 1) & 1][1]);
                }
            }
            publish_o(o, 0, sb, rsb, 4 * r + w, lane);
            TT(n == 7 || n == 0, n ? 1 : 3);
            TQ(n == 7, 0);
            TS(0, n * 16 + 2);
            const uint32_t t2 = clk32();
            while (clk32() - t2 < POST_DELAY) {}
        }
        if (s >= 0) {
            const int lane = fresh_lane(), j = lane & 3;
            uint32_t a[(7 - HOLD) * 16];
            uint32_t t = psl + HOLD >= NSLOT ? psl + HOLD - NSLOT : psl + HOLD;
#pragma unroll
            for (int i = 0; i < 7 - HOLD; i++) {
#pragma unroll
                for (int mt = 0; mt < 4; mt++) {
                    const int q = i * 16 + mt * 4;
                    ldsm4t(a[q], a[q + 1], a[q + 2], a[q + 3], (voff + t * SLOT) ^ (mt << 5));
                }
                t = next_slot(t);
            }
            xch_recv(v2, xin + (2 + (s & 1)) * 128, tag2);
            TQ(s == 7, 3);
            softmax4<false>(s2, v2);
            publish_ml(s2, 1, sb, rsb, 4 * r + w, lane);
            TS(0, s * 16 + 7);
#pragma unroll
            for (int mt = 0; mt < 4; mt++) o[mt][0] = o[mt][1] = o[mt][2] = o[mt][3] = 0.f;
#pragma unroll
            for (int k = 0; k < 8; k++) {
                const uint32_t b0 = __shfl_sync(0xffffffffu, s2[k & 1], 4 * j + (k >> 1));
                const uint32_t b1 = __shfl_sync(0xffffffffu, s2[k & 1], 4 * j + 16 + (k >> 1));
                const uint32_t* vf = k < HOLD ? hold + k * 16 : k < 7 ? a + (k - HOLD) * 16 : hold;
#pragma unroll
                for (int mt = 0; mt < 4; mt++) mma(o[mt], vf[4 * mt], vf[4 * mt + 1], vf[4 * mt + 2], vf[4 * mt + 3], b0, b1);
                if (k == 0) {
#pragma unroll
                    for (int mt = 0; mt < 4; mt++) ldsm4t(hold[4 * mt], hold[4 * mt + 1], hold[4 * mt + 2], hold[4 * mt + 3], (voff + t * SLOT) ^ (mt << 5));
                }
            }
            publish_o(o, 1, sb, rsb, 4 * r + w, lane);
            TS(0, s * 16 + 8); TQ(s == 7, 4);
        }
        if (n == NB) { sign_off(sb); TQ_FLUSH(); break; }
        {
            const int lane = fresh_lane();
            const uint32_t back = ksl + NSLOT - 1 - lane;
            mbar_arrive_if(s >= 0 && lane < 8 - HOLD, bars + (BAR_EMPTY + (back >= NSLOT ? back - NSLOT : back)) * 8);
            uint32_t t = ksl;
#pragma unroll
            for (int ch = 0; ch < HOLD; ch++) {
                const uint32_t base = koff + t * SLOT;
#pragma unroll
                for (int ks = 0; ks < 4; ks++) {
                    const int q = ch * 16 + ks * 4;
                    ldsm4(hold[q], hold[q + 1], hold[q + 2], hold[q + 3], base ^ (ks << 5));
                }
                t = next_slot(t);
            }
            psl = release_slots<HOLD>(bars, ksl, lane, hold, zero);
            TS(0, n * 16 + 3);
        }
        ksl = sl; kpar = par;
    }
}

#undef TQW
#define TQW 4
__device__ __forceinline__ void chain_bar(uint32_t dep) { asm volatile("bar.sync %0, 256;" ::"r"(1 + dep) : "memory"); }
__device__ __forceinline__ void x_bar() { asm volatile("bar.sync 2, 288;" ::: "memory"); }

template <int OFF>
__device__ __forceinline__ void red_out(bool on, const uint4* p, const float (&v)[3]) {
    asm volatile("{\n.reg .pred p;\nsetp.ne.u32 p, %6, 0;\n@p red.relaxed.gpu.global.add.v4.f32 [%0+%5], {%1,%2,%3,%4};\n}"
                 ::"l"(p), "f"(v[0]), "f"(v[1]), "f"(v[2]), "f"(1.0f), "n"(OFF), "r"((uint32_t)on) : "memory");
}

template <int OFF>
__device__ __forceinline__ float4 ld_sum(const uint4* p) {
    float4 v;
    asm volatile("ld.relaxed.gpu.global.v4.f32 {%0,%1,%2,%3}, [%4+%5];" : "=f"(v.x), "=f"(v.y), "=f"(v.z), "=f"(v.w) : "l"(p), "n"(OFF) : "memory");
    return v;
}
template <int OFF>
__device__ __forceinline__ void ld_sum_if(uint32_t on, const uint4* p, float4& v) {
    asm volatile("{\n.reg .pred p;\nsetp.ne.u32 p, %6, 0;\n@p ld.relaxed.gpu.global.v4.f32 {%0,%1,%2,%3}, [%4+%5];\n}"
                 : "+f"(v.x), "+f"(v.y), "+f"(v.z), "+f"(v.w) : "l"(p), "n"(OFF), "r"((uint32_t)on) : "memory");
}
template <int OFF>
__device__ __forceinline__ void poll_sum(const uint4* p, float4 v, float count, uint32_t& y01, uint32_t& y2x) {
    while (!__all_sync(0xffffffffu, v.w == count)) v = ld_sum<OFF>(p);
    y01 = pack2(v.x, v.y); y2x = pack2(v.z, 0.f);
}
template <int OFF, bool BIAS, bool LOOKED>
__device__ __forceinline__ void poll_residual(const uint4* p, const float4& first, float count, uint32_t xrow, int w, uint32_t t0, uint32_t b01, uint32_t b2x,
                                              int lane, uint32_t (&pin)[3], uint32_t zero) {
    const uint32_t tie = clk32() & zero;
    const uint32_t xa = (xrow + w * 80 + (lane & 1) * 48 + (lane >> 2) * 2) | tie;
    uint32_t x01 = lds16(xa) | (lds16(xa + 16) << 16), x2x = lds16(xa + 32), y01, y2x;
#pragma unroll
    for (int i = 0; i < 3; i++) pin[i] |= tie;
    const uint32_t wait = POLL_DELAY + __shfl_sync(0xffffffffu, (pin[0] | pin[1] | pin[2]) & zero, 0);
    while (clk32() - t0 < wait) {}
    poll_sum<OFF>(p, LOOKED ? first : ld_sum<OFF>(p), count, y01, y2x);
    if (BIAS) { y01 = badd2(y01, b01); y2x = badd2(y2x, b2x); }
    x01 = badd2(x01, y01); x2x = badd2(x2x, y2x);
    asm volatile("{\n.reg .pred p;\n.reg .b16 a, b, c, d;\nsetp.eq.u32 p, %3, 0;\nmov.b32 {a, b}, %1;\nmov.b32 {c, d}, %2;\n"
                 "st.shared.b16 [%0], a;\nst.shared.b16 [%0+16], b;\n@p st.shared.b16 [%0+32], c;\n}"
                 ::"r"(xa), "r"(x01), "r"(x2x), "r"(lane & 1) : "memory");
}

template <int K, int OFF>
__device__ __forceinline__ void stage_wo(const uint32_t (&WO)[40], uint32_t par, const uint4* acc, uint32_t sb, int w,
                                         float4& first, uint32_t look, uint32_t zero, bool tq) {
    const int lane = fresh_lane(), g = lane >> 2, j = lane & 3;
    const uint32_t ob = sb + OFF_O + K * 1024 + g * 128 + j * 32 + (g & 1) * 16, ml = sb + OFF_ML + K * 64 + j * 16;
    float e0, e1, inv;
    auto factors = [&]() {
        const float4 mm = lds128f(ml);
        float M = fmaxf(mm.x, mm.z);
        M = fmaxf(M, __shfl_xor_sync(0xffffffffu, M, 1));
        M = fmaxf(M, __shfl_xor_sync(0xffffffffu, M, 2));
        e0 = ex2(mm.x - M); e1 = ex2(mm.z - M);
        float L = e0 * mm.y + e1 * mm.w;
        L += __shfl_xor_sync(0xffffffffu, L, 1);
        L += __shfl_xor_sync(0xffffffffu, L, 2);
        inv = rcp(L) * 16777216.f;
    };
    if (K == 0) {
        mbar_wait(sb + OFF_BAR + BAR_M * 8, par);
        factors();
        mbar_expect_if(w + lane == 0, sb + OFF_BAR + BAR_M * 8, TX_M);
        e0 *= inv; e1 *= inv;
    }
    mbar_wait(sb + OFF_BAR + (BAR_O + K) * 8, par);
    TQ(tq, K * 10 + 0);
    const uint4 B0 = lds128(ob), B1 = lds128(ob ^ 16);
    if (K == 1) factors();
    mbar_expect_if(w + lane == 0, sb + OFF_BAR + (BAR_O + K) * 8, K ? TX_O + TX_M : TX_O);
    const uint32_t B[8] = {B0.x, B0.y, B0.z, B0.w, B1.x, B1.y, B1.z, B1.w};
    float t0[4] = {0.f, 0.f, 0.f, 0.f}, t1[4] = {0.f, 0.f, 0.f, 0.f}, t2[4] = {0.f, 0.f, 0.f, 0.f}, t3[4] = {0.f, 0.f, 0.f, 0.f};
#pragma unroll
    for (int s = 0; s < 4; s++) {
        mma(t0, WO[4 * s], WO[4 * s + 1], WO[4 * s + 2], WO[4 * s + 3], B[2 * s], B[2 * s + 1]);
        mma(t1, WO[16 + 4 * s], WO[16 + 4 * s + 1], WO[16 + 4 * s + 2], WO[16 + 4 * s + 3], B[2 * s], B[2 * s + 1]);
        mma((s & 1) ? t3 : t2, WO[32 + 2 * (s & 2)], WO[33 + 2 * (s & 2)], WO[34 + 2 * (s & 2)], WO[35 + 2 * (s & 2)], B[2 * s], B[2 * s + 1]);
    }
    float v[6] = {e0 * t0[0] + e1 * t0[1], e0 * t0[2] + e1 * t0[3], e0 * t1[0] + e1 * t1[1],
                  e0 * t1[2] + e1 * t1[3], e0 * (t2[0] + t3[2]) + e1 * (t2[1] + t3[3]), 0.f};
    if (K == 1) ld_sum_if<HOP>(look | (__float_as_uint(v[LOOK_V]) & zero), acc, first);
    float u[3];
    const bool odd = j & 1;
#pragma unroll
    for (int i = 0; i < 3; i++) u[i] = (odd ? v[3 + i] : v[i]) + __shfl_xor_sync(0xffffffffu, odd ? v[i] : v[3 + i], 1);
#pragma unroll
    for (int i = 0; i < 3; i++) u[i] = (u[i] + __shfl_xor_sync(0xffffffffu, u[i], 2)) * (K == 1 ? inv : 1.f);
    red_out<OFF>(j < 2, acc, u);
}

template <int K, int OFF>
__device__ __forceinline__ void stage_mlp(const uint32_t (&W1)[20], const uint32_t (&W2)[20], float cs1, uint32_t b2x, uint32_t par,
                                          uint32_t xrow, const uint4* acc, uint32_t t0, uint32_t sb, uint32_t rsb, int r, int w,
                                          bool active, bool last, uint32_t zero, uint32_t b01, uint16_t* out, bool tq) {
    const int lane = fresh_lane(), g = lane >> 2, j = lane & 3, ht = w & 3, kh = w >> 2;
    constexpr uint32_t hb = OFF_H + K * H_SZ, bar = OFF_BAR + (BAR_H + K) * 8;
    const uint32_t jsb = (j & 1) ? rsb : sb;
    uint32_t ad[3] = {xrow + (g & 1) * 320 + j * 16 + kh * 192, jsb + hb + (2 * r + kh) * 128 + (8 * ht + g) * 4, jsb + bar};
    poll_residual<OFF - HOP, false, false>(acc, make_float4(0.f, 0.f, 0.f, 0.f), 64.f, xrow, w, t0, 0, 0, lane, ad, zero);
    TS(1, (xrow - sb - OFF_X) / 40 + (K ? 6 : 1));
    TQ(tq, K * 10 + 2);
    if (!active) return;
    x_bar();
    TQ(tq, K * 10 + 3);
    const uint4 B0 = lds128_if(g < 4, ad[0]);
    const uint2 B2 = lds64_if(g < 4, ad[0] + (128 - kh * 184));
    const uint4 B1 = lds128_if(g < 4, ad[0] + 64);
    float a[4] = {0.f, 0.f, 0.f, 0.f}, b[4] = {0.f, 0.f, 0.f, 0.f}, d[4] = {0.f, 0.f, 0.f, 0.f};
    mma(a, W1[0], W1[1], W1[2], W1[3], B0.x, B0.y);
    mma(b, W1[4], W1[5], W1[6], W1[7], B0.z, B0.w);
    mma(d, W1[16], W1[17], W1[18], W1[19], B2.x, B2.y);
    mma(a, W1[8], W1[9], W1[10], W1[11], B1.x, B1.y);
    mma(b, W1[12], W1[13], W1[14], W1[15], B1.z, B1.w);
    st_async_if(j < 2, ad[1], __float_as_uint(((d[0] + d[3]) + (a[0] + a[3])) + (b[0] + b[3])), ad[2]);
    TQ(tq, K * 10 + 4);
    const float b1v = __uint_as_float(b2x & (0xffff0000u | (lane & zero)));
    mbar_wait(sb + bar, par);
    TQ(tq, K * 10 + 5);
    float4 su = lds128f(sb + hb + 544), q0 = lds128f(sb + hb + 512), q1 = lds128f(sb + hb + 528);
    const uint32_t ha = sb + hb + lane * 4;
    const float4 hp = make_float4(lds32f(ha), lds32f(ha + 128), lds32f(ha + 256), lds32f(ha + 384));
    mbar_expect_if(w + lane == 0, sb + bar, TX_H);
    if (K == 1) mbar_arrive_if(last && lane == 0, sb + OFF_BAR + BAR_DONE * 8);
    float mean = ((su.x + su.y) + (su.z + su.w)) * (1.f / DM);
    float var = fmaxf((((q0.x + q0.y) + (q0.z + q0.w)) + ((q1.x + q1.y) + (q1.z + q1.w))) * (1.f / DM) - mean * mean, 0.f);
    float rs = rsq(fmaf(var, 1.f + LN_EPS, LN_EPS * LN_EPS));
    float pre = fmaf(((hp.x + hp.y) + (hp.z + hp.w)) - mean * cs1, rs, b1v);
    float u2 = pre * fmaf(pre * pre, -2.f * LOG2E * 0.7978845608028654f * 0.044715f, -2.f * LOG2E * 0.7978845608028654f);
    float h0 = pre * rcp(1.f + ex2(u2));
    float h1 = __shfl_xor_sync(0xffffffffu, h0, 8), h2 = __shfl_xor_sync(0xffffffffu, h0, 16), h3 = __shfl_xor_sync(0xffffffffu, h0, 24);
    const uint32_t b0 = pack2(h0, h1), b1 = pack2(h2, h3);
    float v[5];
#pragma unroll
    for (int e = 0; e < 5; e++) {
        float t[4] = {0.f, 0.f, 0.f, 0.f};
        mma(t, W2[4 * e], W2[4 * e + 1], W2[4 * e + 2], W2[4 * e + 3], b0, b1);
        v[e] = t[0] + t[3];
    }
    const bool odd = j & 1;
    float u[3] = {odd ? v[3] : v[0], odd ? v[4] : v[1], odd ? 0.f : v[2]};
    if (K == 0 || out == nullptr) {
        red_out<OFF>(j < 2, acc, u);
    } else if (j < 2) {
        float4 o;
        asm volatile("atom.relaxed.gpu.global.add.v4.f32 {%0,%1,%2,%3}, [%4+%9], {%5,%6,%7,%8};"
                     : "=f"(o.x), "=f"(o.y), "=f"(o.z), "=f"(o.w) : "l"(acc), "f"(u[0]), "f"(u[1]), "f"(u[2]), "f"(1.0f), "n"(OFF) : "memory");
        const int col = w * 40 + j * 24 + g;
        const uint32_t xa = xrow + col * 2;
        uint32_t x01 = lds16(xa) | (lds16(xa + 16) << 16), x2x = lds16(xa + 32);
        x01 = badd2(x01, badd2(pack2(o.x + u[0], o.y + u[1]), b01));
        x2x = badd2(x2x, badd2(pack2(o.z + u[2], 0.f), b2x));
        if (o.w == (float)(ACT_PAIRS - 1)) {
            out[col] = (uint16_t)x01;
            out[col + 8] = (uint16_t)(x01 >> 16);
            if (!odd) out[col + 16] = (uint16_t)x2x;
        }
    }
    if (K == 1) __syncwarp();
}

__device__ __forceinline__ void chain_role(const Params& P, uint32_t sb, uint32_t rsb, int w, int lane) {
    const int c = blockIdx.x, r = c & 1, p = c >> 1;
    const int g = lane >> 2, j = lane & 3, mi = lane >> 3, ri = lane & 7;
    const uint32_t bars = sb + OFF_BAR;
    const uint32_t jsb = (j & 1) ? rsb : sb;
    const bool active = p < ACT_PAIRS, odd = j & 1;
    uint32_t WQ[40], WO[40], W1[20], W2[20];

    uint32_t x0[5];
    {
        const uint32_t* xr = reinterpret_cast<const uint32_t*>(P.x + w * DM);
        uint32_t xw[10];
#pragma unroll
        for (int i = 0; i < 10; i++) xw[i] = __ldg(xr + lane + 32 * i);
        float sum = 0.f;
#pragma unroll
        for (int i = 0; i < 10; i++) sum += __uint_as_float(xw[i] << 16) + __uint_as_float(xw[i] & 0xffff0000u);
        const float mean = warp_sum(sum) * (1.f / DM);
        float sq = 0.f;
#pragma unroll
        for (int i = 0; i < 10; i++) {
            float d0 = __uint_as_float(xw[i] << 16) - mean, d1 = __uint_as_float(xw[i] & 0xffff0000u) - mean;
            sq += d0 * d0 + d1 * d1;
        }
        const float mb = rbf(mean), den = rbf(fsqrt(rbf(rbf(warp_sum(sq) * (1.f / DM)) + LN_EPS)));
#pragma unroll
        for (int i = 0; i < 5; i++) {
            uint32_t v = r ? xw[5 + i] : xw[i];
            float d0 = rbf(__uint_as_float(v << 16) - mb), d1 = rbf(__uint_as_float(v & 0xffff0000u) - mb);
            x0[i] = v;
            sts32(sb + OFF_X + w * 640 + (lane + 32 * i) * 4, pack2(fdiv(d0, den), fdiv(d1, den)));
        }
    }
    const int col = 40 * w + 24 * (j & 1) + g;
    uint32_t b01, b2x;
    {
        const uint16_t* pb2 = reinterpret_cast<const uint16_t*>(P.b2) + 320 * r + col;
        b01 = (uint32_t)pb2[0] | ((uint32_t)pb2[8] << 16);
        b2x = (odd ? 0u : (uint32_t)pb2[16]) | (active ? (uint32_t)reinterpret_cast<const uint16_t*>(P.b1)[32 * p + lane] << 16 : 0u);
    }
    cluster_wait();
#pragma unroll 1
    for (int i = 0; i < 5; i++) mbar_wait(bars + i * 8, 0);
#pragma unroll
    for (int t = 0; t < 10; t++) {
        int k = (mi & 1) * 160 + 32 * (t >> 1) + 8 * (ri >> 1) + 2 * (2 * (t & 1) + (mi >> 1)) + (ri & 1);
        ldsm4t(WQ[4 * t], WQ[4 * t + 1], WQ[4 * t + 2], WQ[4 * t + 3], sb + k * 128 + ((w ^ (k & 7)) << 4));
        if (WGAP) __nanosleep(2 * WGAP);
    }
    uint32_t dep = 0;
#pragma unroll
    for (int t = 0; t < 10; t++) dep |= WQ[4 * t];
    TS(1, 200);
    chain_bar(dep & P.zero);
    mbar_arrive_if(w < 4 && lane < 5, bars + (BAR_EMPTY + lane) * 8);
    {
        const uint32_t pb = OFF_BAR + BAR_P * 8, off = OFF_O + (j * 64 + 8 * w + g) * 4;
        float qp[3];
#pragma unroll
        for (int rd = 0; rd < 3; rd++) {
            const uint32_t xb = sb + OFF_X + (4 * rd + (g >> 1)) * 640 + (g & 1) * 320 + j * 16;
            float a[4] = {0.f, 0.f, 0.f, 0.f};
#pragma unroll
            for (int blk = 0; blk < 5; blk++) {
                const uint4 B = rd < 2 ? lds128(xb + blk * 64) : make_uint4(ONES, ONES, ONES, ONES);
                mma(a, WQ[8 * blk], WQ[8 * blk + 1], WQ[8 * blk + 2], WQ[8 * blk + 3], B.x, B.y);
                mma(a, WQ[8 * blk + 4], WQ[8 * blk + 5], WQ[8 * blk + 6], WQ[8 * blk + 7], B.z, B.w);
            }
            qp[rd] = a[0] + a[3];
            st_async_if(rd < 2 || j == 0, rsb + off + rd * 1024, __float_as_uint(qp[rd]), rsb + pb);
        }
        chain_bar(0);
#pragma unroll
        for (int i = 0; i < 5; i++) sts32(sb + OFF_X + w * 640 + (lane + 32 * i) * 4, x0[i]);
        mbar_wait(sb + pb, 0);
#pragma unroll
        for (int rd = 0; rd < 2; rd++) {
            const float q = qp[rd] + lds32f(sb + off + rd * 1024), qn = __shfl_xor_sync(0xffffffffu, q, 4);
            if (!(g & 1)) sts32(sb + OFF_Q1 + (4 * rd + j) * 128 + ((g >> 1) * 8 + w) * 4, pack2(q, qn));
        }
        if (j == 0) sts32(sb + OFF_CSQ + (8 * w + g) * 4, __float_as_uint(qp[2] + lds32f(sb + off + 2048)));
        __syncwarp();
        mbar_arrive_if(lane == 0, bars + BAR_Q1 * 8);
        asm volatile("{\n.reg .pred p;\nsetp.eq.u32 p, %1, 0;\n@p mbarrier.arrive.relaxed.cluster.shared::cluster.b64 _, [%0];\n}"
                     ::"r"(rsb + OFF_BAR + BAR_Q1 * 8), "r"(lane) : "memory");
    }
    TS(1, 201);
#pragma unroll 1
    for (int i = 5; i < 10; i++) mbar_wait(bars + i * 8, 0);
#pragma unroll
    for (int t = 0; t < 10; t++) {
        int cc = 5 * w + (t < 8 ? 2 * (t >> 2) + (mi & 1) : 4);
        int k = 16 * (ri >> 1) + 8 * (ri & 1) + (((t < 8 ? 2 * (t & 3) : 4 * (t - 8) + 2 * (mi & 1)) + (mi >> 1) + (ri & 6)) & 7);
        ldsm4t(WO[4 * t], WO[4 * t + 1], WO[4 * t + 2], WO[4 * t + 3],
               sb + (5 + (cc >> 3)) * SLOT + k * 128 + (((cc & 7) ^ (k & 7)) << 4));
        if (WGAP) __nanosleep(WGAP);
    }
#pragma unroll 1
    for (int i = 10; i < 15; i++) mbar_wait(bars + i * 8, 0);
#pragma unroll
    for (int t = 0; t < 5; t++) {
        int k = (mi & 1) * 160 + 8 * (ri >> 1) + 2 * (mi >> 1) + (ri & 1) +
                (t < 4 ? (w >> 2) * 96 + 32 * (t >> 1) + 4 * (t & 1) : 64 + 4 * (w >> 2));
        ldsm4t(W1[4 * t], W1[4 * t + 1], W1[4 * t + 2], W1[4 * t + 3], sb + (10 + (k >> 6)) * SLOT + (k & 63) * 64 + (w & 3) * 16);
        int cc = 5 * w + t, k2 = 4 * (mi & 1) + (ri >> 1) + 8 * ((2 * (mi >> 1) + (ri & 1)) ^ (t >= 3));
        ldsm4t(W2[4 * t], W2[4 * t + 1], W2[4 * t + 2], W2[4 * t + 3],
               sb + (10 + (cc >> 3)) * SLOT + 4096 + k2 * 128 + (((cc & 7) ^ (k2 & 7)) << 4));
        if (WGAP) __nanosleep(3 * WGAP);
    }
#pragma unroll
    for (int t = 0; t < 10; t++) dep |= WO[4 * t] | (t < 5 ? W1[4 * (t % 5)] : W2[4 * (t % 5)]);
    chain_bar(dep & P.zero);
    TS(1, 202);
    mbar_arrive_if(w < 4 && lane < 10, bars + (BAR_EMPTY + 5 + lane) * 8);
    float cs1;
    {
        float a[4] = {0.f, 0.f, 0.f, 0.f};
#pragma unroll
        for (int t = 0; t < 5; t++) mma(a, W1[4 * t], W1[4 * t + 1], W1[4 * t + 2], W1[4 * t + 3], ONES, ONES);
        const uint32_t hb = OFF_H + H_SZ, bar = OFF_BAR + (BAR_H + 1) * 8;
        st_async_if(j < 2, jsb + hb + (2 * r + (w >> 2)) * 128 + (8 * (w & 3) + g) * 4, __float_as_uint(a[0] + a[3]), jsb + bar);
        mbar_wait(sb + bar, 0);
        const uint32_t ha = sb + hb + lane * 4;
        const float4 hp = make_float4(lds32f(ha), lds32f(ha + 128), lds32f(ha + 256), lds32f(ha + 384));
        mbar_expect_if(w + lane == 0, sb + bar, TX_H);
        cs1 = (hp.x + hp.y) + (hp.z + hp.w);
    }
    b01 = __shfl_sync(0xffffffffu, b01, lane);
    b2x = __shfl_sync(0xffffffffu, b2x, lane);
    const uint4* acc = g_acc + acc_index(r * 128 + w * 16 + 2 * g + (j & 1));
    uint32_t xrow = sb + OFF_X;

#pragma unroll 1
    for (int s = 0; s <= NB; ++s, acc += HOP / 4, xrow += 640) {
        uint32_t t0 = 0;
        float4 first = make_float4(0.f, 0.f, 0.f, 0.f);
        if (s < NB) {
            stage_wo<0, 0>(WO, s & 1, acc, sb, w, first, 0, 0, s == 7);
            TQ(s == 7, 1);
            t0 = clk32();
            TS(1, s * 16 + 0);
            stage_mlp<0, HOP>(W1, W2, cs1, b2x, s & 1, xrow, acc, t0, sb, rsb, r, w, active, false, P.zero, 0, nullptr, s == 7);
            TQ(s == 7, 6);
            t0 = clk32();
            TS(1, s * 16 + 2);
        }
        if (s >= 1) {
            stage_wo<1, -2 * HOP>(WO, (s - 1) & 1, acc, sb, w, first, s < NB, P.zero, s == 8);
            TQ(s == 8, 11); TQ(s == 7, 20);
            if (s == NB) t0 = clk32();
            TS(1, (s - 1) * 16 + 5);
        }
        if (s < NB) {
            const int ln = fresh_lane();
            const uint32_t qsb = (ln & 1) ? rsb : sb;
            uint32_t ad[3] = {xrow + (ln & 4) * 80 + (ln & 3) * 16, qsb + OFF_Q + r * 256 + (8 * w + (ln >> 2)) * 4, qsb + OFF_BAR + BAR_Q * 8};
            poll_residual<HOP, true, true>(acc, first, (float)ACT_PAIRS, xrow, w, t0, b01, b2x, ln, ad, P.zero);
            TS(1, s * 16 + 3); TQ(s == 7, 7);
            x_bar();
            TQ(s == 7, 8);
            float a[4] = {0.f, 0.f, 0.f, 0.f}, b[4] = {0.f, 0.f, 0.f, 0.f}, d[4] = {0.f, 0.f, 0.f, 0.f};
#pragma unroll
            for (int blk = 0; blk < 5; blk++) {
                const uint4 B = lds128_if(ln < 16, ad[0] + blk * 64);
                mma((2 * blk) % 3 == 0 ? a : (2 * blk) % 3 == 1 ? b : d, WQ[8 * blk], WQ[8 * blk + 1], WQ[8 * blk + 2], WQ[8 * blk + 3], B.x, B.y);
                mma((2 * blk + 1) % 3 == 0 ? a : (2 * blk + 1) % 3 == 1 ? b : d, WQ[8 * blk + 4], WQ[8 * blk + 5], WQ[8 * blk + 6], WQ[8 * blk + 7], B.z, B.w);
            }
            st_async_if((ln & 2) == 0, ad[1], __float_as_uint(((b[0] + b[3]) + (d[0] + d[3])) + (a[0] + a[3])), ad[2]);
            TS(1, s * 16 + 4); TQ(s == 7, 9);
        }
        if (s >= 1 && active) {
            stage_mlp<1, -HOP>(W1, W2, cs1, b2x, s & 1, xrow - 640, acc, t0, sb, rsb, r, w, true, s == NB, P.zero, b01,
                               (s == 1 || s == NB) ? reinterpret_cast<uint16_t*>(P.out) + (s - 1) * DM + 320 * r : nullptr, s == 8);
            TT(s == NB, 2);
            TQ(s == 8, 16); TQ(s == 7, 21);
            TS(1, (s - 1) * 16 + 7);
        }
    }
    if (!active) sign_off(sb);
    TQ_FLUSH();
}

__device__ __forceinline__ void moments_role(const Params& P, uint32_t sb, uint32_t rsb) {
    const int c = blockIdx.x, r = c & 1, p = c >> 1;
    const bool active = p < ACT_PAIRS, writer = !active && p < OUT_PAIR + 4;
    constexpr int w = 9; (void)w;
#pragma unroll 1
    for (int i = 0; i < 3 * (NB + 1); i++) {
        const int s = i / 3, ph = i - 3 * s;
        const int lane = fresh_lane(), g = lane >> 2, j = lane & 3;
        if (ph == 2 && writer && s >= 3) {
            const int b = s - 2, vec = (p - OUT_PAIR) * 32 + lane, col = 40 * (vec >> 4) + 24 * (vec & 1) + ((vec >> 1) & 7);
            const uint4* acc = g_acc + acc_index(r * 128 + vec) + b * (HOP / 4);
            const uint16_t* pb = reinterpret_cast<const uint16_t*>(P.b2) + 320 * r + col;
            const uint32_t xa = sb + OFF_X + b * 640 + col * 2;
            uint32_t x01 = lds16(xa) | (lds16(xa + 16) << 16), x2x = lds16(xa + 32), y01, y2x;
            const uint32_t b01 = (uint32_t)pb[0] | ((uint32_t)pb[8] << 16), b2x = pb[(vec & 1) ? 8 : 16];
            poll_sum<2 * HOP>(acc, ld_sum<2 * HOP>(acc), 64.f, y01, y2x);
            x01 = badd2(x01, y01); x2x = badd2(x2x, y2x);
            poll_sum<3 * HOP>(acc, ld_sum<3 * HOP>(acc), (float)ACT_PAIRS, y01, y2x);
            x01 = badd2(x01, badd2(y01, b01)); x2x = badd2(x2x, badd2(y2x, b2x));
            uint16_t* o = reinterpret_cast<uint16_t*>(P.out) + b * DM + 320 * r + col;
            o[0] = (uint16_t)x01;
            o[8] = (uint16_t)(x01 >> 16);
            if (!(vec & 1)) o[16] = (uint16_t)x2x;
            __syncwarp();
            TS(1, b * 16 + 8);
        }
        if (ph == 2 ? (s == 0 || !active) : (s >= NB || (ph == 0 && !active))) continue;
        const uint32_t xb = sb + OFF_X + (g & 1) * 320 + (g & 2) * 96 + j * 16 + (ph == 2 ? s - 1 : s) * 640;
        const uint32_t xc = xb + 128 - (g & 2) * 92;
        const bool diag = g < 4 && j == (g >> 1), side = g == 4 && j < 2;
        const uint32_t dst = (ph == 1 ? OFF_Q : ph == 0 ? OFF_H : OFF_H + H_SZ) + 512 + (diag ? (r * 4 + g) * 4 : 32 + (r * 2 + j) * 4);
        const uint32_t bar = OFF_BAR + (ph == 1 ? BAR_Q : ph == 0 ? BAR_H : BAR_H + 1) * 8;
        asm volatile("bar.sync %0, 288;" ::"r"(2 + ((xb | xc | dst) & P.zero)) : "memory");
        const uint4 B0 = lds128_if(g < 4, xb);
        const uint4 B1 = lds128_if(g < 4, xb + 64);
        const uint2 B2 = lds64_if(g < 4, xc);
        float a[4] = {0.f, 0.f, 0.f, 0.f}, b[4] = {0.f, 0.f, 0.f, 0.f}, d[4] = {0.f, 0.f, 0.f, 0.f};
        mma(a, B0.x, ONES, B0.y, ONES, B0.x, B0.y);
        mma(b, B0.z, ONES, B0.w, ONES, B0.z, B0.w);
        mma(d, B1.x, ONES, B1.y, ONES, B1.x, B1.y);
        mma(a, B1.z, ONES, B1.w, ONES, B1.z, B1.w);
        mma(b, B2.x, ONES, B2.y, ONES, B2.x, B2.y);
        const float vd = diag ? ((g & 1) ? d[1] : d[0]) : d[2] + d[3], va = diag ? ((g & 1) ? a[1] : a[0]) : a[2] + a[3];
        const float vb = diag ? ((g & 1) ? b[1] : b[0]) : b[2] + b[3];
        if (diag || side) {
            st_async(rsb + dst, __float_as_uint((vd + va) + vb), rsb + bar);
            st_async(sb + dst, __float_as_uint((vd + va) + vb), sb + bar);
        }
        __syncwarp();
        TQ(i == 21, 0); TQ(i == 22, 1); TQ(i == 26, 2);
    }
    TQ_FLUSH();
}

struct Maps { CUtensorMap k, v, wq, wo, w1, w2; };

__device__ __forceinline__ void cluster_arrive() {
    asm volatile("fence.mbarrier_init.release.cluster;\nfence.acq_rel.cta;\nbarrier.cluster.arrive.relaxed.aligned;" ::: "memory");
}

__device__ __forceinline__ void weights_role(const Maps& M, uint32_t sb) {
    const int c = blockIdx.x, p = c >> 1;
    uint64_t pol;
    asm("createpolicy.fractional.L2::evict_first.b64 %0, 1.0;" : "=l"(pol));
    int v = 320 * (c & 1);
#pragma unroll 1
    for (int i = 0; i < NWI; i++) {
        const uint32_t bar = sb + OFF_BAR + i * 8, dst = sb + i * SLOT;
        if (i < NTOP) {
            if (elect_one()) mbar_init(bar, 1);
            asm volatile("fence.mbarrier_init.release.cluster;" ::: "memory");
        } else {
            if (i == NTOP) { cluster_arrive(); cluster_wait(); }
            mbar_wait(bar - NTOP * 8, 0);
        }
        const bool wo = i >= 5 && i < 10;
        const int u = i < 10 ? 64 * p : 32 * p;
        if (elect_one()) {
            mbar_expect(bar, SLOT);
            tma2d(dst, &M.wq + (i < 5 ? 0 : i < 10 ? 1 : 2), wo ? v : u, wo ? u : v, bar, pol);
            if (i >= 10) tma2d(dst + 4096, &M.w2, v, u, bar, pol);
        }
        v += (i == 4 || i == 9) ? -256 : 64;
        TS(2, i);
    }
}
static_assert(NTOP >= WSTART && NTOP < NWI && WSTART == WMAX, "start window");

__device__ __forceinline__ void producer_role(const Maps& M, uint32_t sb) {
    const int c = blockIdx.x;
    const uint32_t bars = sb + OFF_BAR;
    uint64_t pol;
    asm("createpolicy.fractional.L2::evict_first.b64 %0, 1.0;" : "=l"(pol));
    const int x = (c & 2) * 32, y0 = (c >> 2) * SK + (SK - WIN) + (c & 1) * 512;
    uint32_t dst = sb + NWI * SLOT, bar = bars + NWI * 8, epar = 1;
    uint32_t wbar = bars + (NWI - WSTART) * 8, wpar = 0;
    int win = WSTART;
#pragma unroll 1
    for (int ii = 0; ii < NB * 16; ii++) {
        mbar_wait(bar + BAR_EMPTY * 8, epar);
        if (elect_one()) mbar_expect(bar, SLOT);
        const CUtensorMap* tm = (ii & 8) ? &M.v : &M.k;
        const int y = y0 + (ii >> 4) * (32 * SK) + (ii & 7) * 64;
        const bool hi = mbar_test(bars + BAR_WIN * 8, 0), lo = mbar_test(bars + BAR_WIN * 8 + 8, 0);
        const int target = WMAX - (hi ? (lo ? 2 : 3) : (lo ? 1 : 0));
        const int waits = (target > win || ii >= NB * 16 - END_FREE) ? 0 : target < win ? 2 : 1;
        win += 1 - waits;
        if (waits == 2) {
            mbar_wait(wbar, wpar);
            wbar += 8; if (wbar == bars + NSLOT * 8) { wbar = bars; wpar ^= 1; }
        }
        if (waits) mbar_wait(wbar, wpar);
        if (elect_one()) tma2d(dst, tm, x, y, bar, pol);
        TS(2, ii + NWI);
        TT(ii == 16, 5);
        if (waits) { wbar += 8; if (wbar == bars + NSLOT * 8) { wbar = bars; wpar ^= 1; } }
        bar += 8; dst += SLOT;
        if (bar == bars + NSLOT * 8) { bar = bars; dst = sb; epar ^= 1; }
    }
}

__global__ void __cluster_dims__(2, 1, 1) __launch_bounds__(NTHREADS, 1)
fused_decode_kernel(const __grid_constant__ Maps M, const __grid_constant__ Params P) {
    extern __shared__ __align__(1024) unsigned char smem[];
    if (threadIdx.x == 0 && PRE_BYTES) {
        if (PRE_DELAY) { const uint32_t t0 = clk32(); while ((int)(clk32() - t0) < PRE_DELAY) {} }
        asm volatile("cp.async.bulk.prefetch.L2.global [%0], %1;"
                     ::"l"(reinterpret_cast<const char*>(P.wq) + blockIdx.x * 40960), "r"(PRE_BYTES) : "memory");
    }
    const uint32_t sb = (uint32_t)__cvta_generic_to_shared(smem);
    const int lane = threadIdx.x & 31, c = blockIdx.x;
    const int warp = __shfl_sync(0xffffffffu, threadIdx.x >> 5, 0);
    const uint32_t bars = sb + OFF_BAR;
    TT(warp == 15, 0);
    if (lane == 0 && warp >= 1 && warp < 7) asm volatile("prefetch.tensormap [%0];" ::"l"(&M.k + (warp - 1)) : "memory");
    uint32_t rsb;
    asm("mapa.shared::cluster.u32 %0, %1, %2;" : "=r"(rsb) : "r"(sb), "r"((c & 1) ^ 1));

    if (warp < 12) {
        if (lane == 0) {
#pragma unroll 1
            for (int b = NTOP + warp; b < BAR_O; b += 12) mbar_init(bars + b * 8, b < BAR_EMPTY ? 1 : 4);
        }
        __syncwarp();
        cluster_arrive();
        asm volatile("setmaxnreg.inc.sync.aligned.u32 %0;" ::"n"(REG_WORK));
        if (warp < 4) attention_role(sb, rsb, warp, lane, P.zero);
        else chain_role(P, sb, rsb, warp - 4, lane);
    } else {
        asm volatile("setmaxnreg.dec.sync.aligned.u32 %0;" ::"n"(REG_MISC));
        if (warp == 12) {
            cluster_arrive();
            cluster_wait();
            producer_role(M, sb);
            mbar_arrive_if(lane < 2, bars + (BAR_DONE + lane) * 8);
            if (lane == 0) {
            }
        } else if (warp == 14) {
            cluster_arrive();
            TS(2, 200);
#pragma unroll 1
            for (int i = 0; i < XZERO; i++) g_xch[c * 512 + i * 32 + lane] = make_uint4(0, 0, 0, 0);
            g_acc[acc_index((c & 3) * 64 + lane) + (c >> 2) * (HOP / 16)] = make_uint4(0, 0, 0, 0);
            g_acc[acc_index((c & 3) * 64 + 32 + lane) + (c >> 2) * (HOP / 16)] = make_uint4(0, 0, 0, 0);
            if (c == 0 && lane == 0) g_progress = 0;
            __syncwarp();
            cluster_wait();
            if (lane == 0) {
                unsigned seen;
                asm volatile("atom.acq_rel.gpu.global.add.u32 %0, [%1], 1;" : "=r"(seen) : "l"(&g_arrive) : "memory");
                TS(2, 201);
                const unsigned target = (seen / NCTA + 1) * NCTA;
                do {
                    __nanosleep(200);
                    asm volatile("ld.acquire.gpu.global.u32 %0, [%1];" : "=r"(seen) : "l"(&g_arrive) : "memory");
                } while ((int)(seen - target) < 0);
                mbar_arrive(bars + BAR_INIT * 8);
                TS(2, 202);
                int mine = 0, told = 0, code = 0;
                uint32_t fb = bars + NWI * 8, fp = 0;
                do {
                    while (mine < NB * 16 && mbar_test(fb, fp)) {
                        mine++;
                        fb += 8; if (fb == bars + NSLOT * 8) { fb = bars; fp ^= 1; }
                    }
                    int all;
                    asm volatile("atom.relaxed.gpu.global.add.u32 %0, [%1], %2;" : "=r"(all) : "l"(&g_progress), "r"(mine - told) : "memory");
                    const int lag = all - mine * NCTA + LEAD_BIAS;
                    const int less = WMAX - min(max(WINDOW + (lag + 256 * LEAD_STEP) / LEAD_STEP - 256, WMAX - 3), WMAX);
                    const int flip = told >= WSHRINK ? code ^ less ^ (less >> 1) : 0;
                    if (flip & 2) mbar_arrive(bars + BAR_WIN * 8);
                    if (flip & 1) mbar_arrive(bars + BAR_WIN * 8 + 8);
                    code ^= flip;
                    told = mine;
                    __nanosleep(PACE_GAP);
                } while (!mbar_test(bars + BAR_END * 8, 0));
                mbar_arrive(bars + BAR_DONE * 8);
            }
        } else if (warp == 15) {
            if (lane == 0) {
#pragma unroll
                for (int b = BAR_O; b <= BAR_WIN + 1; b++) mbar_init(bars + b * 8, b == BAR_Q1 ? 16 : b == BAR_DONE ? 15 : 1);
#pragma unroll
                for (int b = BAR_O; b <= BAR_P; b++)
                    mbar_expect(bars + b * 8, b == BAR_O ? TX_O : b == BAR_O + 1 ? TX_O + TX_M : b == BAR_M ? TX_M : b == BAR_H ? TX_H
                                              : b == BAR_H + 1 ? 512u : b == BAR_Q ? TX_Q : TX_P);
                if (sb & 1023) __trap();
            }
            __syncwarp();
            cluster_arrive();
            cluster_wait();
            const long long t0 = clock64();
            uint32_t done;
            do {
                __nanosleep(250);
                done = mbar_test(bars + BAR_DONE * 8, 0);
                if (clock64() - t0 > WATCHDOG) __trap();
            } while (!done);
        } else {
            weights_role(M, sb);
            moments_role(P, sb, rsb);
            sign_off(sb);
        }
    }
}

typedef CUresult (*EncodeFn)(CUtensorMap*, CUtensorMapDataType, cuuint32_t, void*, const cuuint64_t*, const cuuint64_t*,
                             const cuuint32_t*, const cuuint32_t*, CUtensorMapInterleave, CUtensorMapSwizzle,
                             CUtensorMapL2promotion, CUtensorMapFloatOOBfill);

bool make_map(EncodeFn enc, CUtensorMap* m, const void* base, uint64_t cols, uint64_t rows, uint32_t bx, uint32_t by, bool swz) {
    cuuint64_t gd[2] = {cols, rows}, gs[1] = {cols * 2};
    cuuint32_t box[2] = {bx, by}, es[2] = {1, 1};
    return enc(m, CU_TENSOR_MAP_DATA_TYPE_BFLOAT16, 2, const_cast<void*>(base), gd, gs, box, es, CU_TENSOR_MAP_INTERLEAVE_NONE,
               swz ? CU_TENSOR_MAP_SWIZZLE_128B : CU_TENSOR_MAP_SWIZZLE_NONE, CU_TENSOR_MAP_L2_PROMOTION_L2_128B,
               CU_TENSOR_MAP_FLOAT_OOB_FILL_NONE) == CUDA_SUCCESS;
}

}

extern "C" void kernel_launch(void* const* d_in, const int* in_sizes, int n_in, void* d_out, int out_size) {
    (void)in_sizes; (void)n_in; (void)out_size;
    void* fn = nullptr;
    cudaDriverEntryPointQueryResult qr;
    if (cudaGetDriverEntryPoint("cuTensorMapEncodeTiled", &fn, cudaEnableDefault, &qr) != cudaSuccess || !fn) return;
    EncodeFn enc = (EncodeFn)fn;
    Maps M;
    bool ok = make_map(enc, &M.k, d_in[1], 128, (uint64_t)NB * 32 * SK, 64, 64, true) &&
              make_map(enc, &M.v, d_in[2], 128, (uint64_t)NB * 32 * SK, 64, 64, true) &&
              make_map(enc, &M.wq, d_in[3], 4096, DM, 64, 64, true) &&
              make_map(enc, &M.wo, d_in[4], DM, 4096, 64, 64, true) &&
              make_map(enc, &M.w1, d_in[6], FF, DM, 32, 64, false) &&
              make_map(enc, &M.w2, d_in[8], DM, FF, 64, 32, true);
    cudaFuncAttributes fa;
    ok = ok && cudaFuncGetAttributes(&fa, fused_decode_kernel) == cudaSuccess &&
         fa.numRegs * 4 >= 3 * REG_WORK + REG_MISC;
    if (!ok) return;
    cudaFuncSetAttribute(fused_decode_kernel, cudaFuncAttributeMaxDynamicSharedMemorySize, SMEM_BYTES);
    Params P;
    P.x = (const __nv_bfloat16*)d_in[0];
    P.wq = (const __nv_bfloat16*)d_in[PRE_IN];
    P.b1 = (const __nv_bfloat16*)d_in[7];
    P.b2 = (const __nv_bfloat16*)d_in[9];
    P.out = (__nv_bfloat16*)d_out;
    P.zero = 0;
    fused_decode_kernel<<<NCTA, NTHREADS, SMEM_BYTES>>>(M, P);
}
```

```cpp
#include <cuda_runtime.h>
#include <cuda_bf16.h>
#include <cuda.h>
#include <stdint.h>

namespace {

constexpr int NB = 8, DM = 640, SK = 4096, WIN = 1024, FF = 1728;
constexpr int NCTA = 128, NTHREADS = 512;
constexpr int SLOT = 8192, NSLOT = 27, NWI = 15;
constexpr int ACT_PAIRS = FF / 32;
constexpr int OUT_PAIR = ACT_PAIRS;
#define HOLD 5
#define WINDOW 4
#define POLL_DELAY 310
#define XCH1_DELAY 1400
#define WSHRINK 10
#define LEAD_STEP 224
#define WMAX 6
#define LEAD_BIAS 180
#define PACE_GAP 50
#define XCH2_DELAY 280
#define GRP 4
#define POST_DELAY 350
#define LOOK_V 0
#define WATCHDOG 2000000000LL
#define WAITV 1
#define DOGV 1
#define WW 3
#define LESS0 3
#define XCH_AT 3
constexpr int REG_WORK = 160, REG_MISC = 32;

constexpr int OFF_BAR = NSLOT * SLOT;
constexpr int BAR_EMPTY = NSLOT, BAR_O = 2 * NSLOT, BAR_M = BAR_O + 2, BAR_H = BAR_M + 1, BAR_Q = BAR_H + 2,
              BAR_P = BAR_Q + 1, BAR_Q1 = BAR_P + 1, BAR_INIT = BAR_Q1 + 1, BAR_DONE = BAR_INIT + 1,
              BAR_END = BAR_DONE + 1,
              BAR_WGT = BAR_END + 1,
              BAR_WIN = BAR_WGT + 1;
constexpr int OFF_SINK = OFF_BAR + 576;
constexpr int OFF_O = OFF_BAR + 640;
constexpr int OFF_ML = OFF_O + 2 * 1024;
constexpr int OFF_H = OFF_ML + 128, H_SZ = 576;
constexpr int OFF_Q = OFF_H + 2 * H_SZ;
constexpr int OFF_Q1 = OFF_Q + H_SZ;
constexpr int OFF_CSQ = OFF_Q1 + 1024;
constexpr int OFF_X = OFF_CSQ + 256;
constexpr int SMEM_BYTES = OFF_X + NB * 640 + 32;
static_assert(SMEM_BYTES <= 232448, "smem");
static_assert(BAR_WIN + 1 < 72, "barriers");
constexpr uint32_t TX_O = 8 * 128, TX_M = 8 * 64, TX_H = 2 * (256 + 24), TX_Q = 2 * (256 + 24), TX_P = 9 * 64 * 4;
static_assert(TX_P <= OFF_H + H_SZ - OFF_O, "prologue exchange lives in the O buffers");

constexpr float LN_EPS = 1e-5f;
constexpr float LOG2E = 1.4426950408889634f;
constexpr float SCALE = 0.08838834764831845f;
constexpr uint32_t ONES = 0x3F803F80u;

constexpr int HOP = 32768;
__device__ uint4 g_acc[33 * HOP / 16];
__device__ uint4 g_xch[NCTA * 4 * 128];
__device__ unsigned g_progress;
__device__ unsigned g_arrive;
#define TS(role, idx) do {} while (0)
#define TQ(cond, idx) do {} while (0)
#define TQ_FLUSH() do {} while (0)
#define TT(cond, idx) do {} while (0)

__device__ __forceinline__ uint4* acc_ptr(int v) {
    const uintptr_t base = (reinterpret_cast<uintptr_t>(g_acc) + (HOP - 1)) & ~(uintptr_t)(HOP - 1);
    return reinterpret_cast<uint4*>(base) + (GRP == 4 ? (v >> 3) * 64 + (v & 4) * 4 + (v & 3) : (v >> 3) * 64 + (v & 7));
}
__device__ __forceinline__ uint32_t clk32() { uint32_t c; asm volatile("mov.u32 %0, %%clock;" : "=r"(c)); return c; }
__device__ __forceinline__ void mbar_init(uint32_t bar, uint32_t cnt) {
    asm volatile("mbarrier.init.shared::cta.b64 [%0], %1;" ::"r"(bar), "r"(cnt) : "memory");
}
__device__ __forceinline__ void mbar_expect(uint32_t bar, uint32_t bytes) {
    asm volatile("mbarrier.arrive.expect_tx.shared::cta.b64 _, [%0], %1;" ::"r"(bar), "r"(bytes) : "memory");
}
__device__ __forceinline__ void mbar_arrive(uint32_t bar) {
    asm volatile("mbarrier.arrive.shared::cta.b64 _, [%0];" ::"r"(bar) : "memory");
}
__device__ __forceinline__ void mbar_expect_if(bool on, uint32_t bar, uint32_t bytes) {
    asm volatile("{\n.reg .pred p;\nsetp.ne.u32 p, %2, 0;\n@p mbarrier.arrive.expect_tx.shared::cta.b64 _, [%0], %1;\n}"
                 ::"r"(bar), "r"(bytes), "r"((uint32_t)on) : "memory");
}
__device__ __forceinline__ void mbar_arrive_if(bool on, uint32_t bar) {
    asm volatile("{\n.reg .pred p;\nsetp.ne.u32 p, %1, 0;\n@p mbarrier.arrive.shared::cta.b64 _, [%0];\n}" ::"r"(bar), "r"((uint32_t)on) : "memory");
}
__device__ __forceinline__ bool mbar_test(uint32_t bar, uint32_t parity) {
    uint32_t ok;
    asm volatile("{\n.reg .pred p;\nmbarrier.test_wait.parity.shared::cta.b64 p, [%1], %2;\nselp.u32 %0, 1, 0, p;\n}"
                 : "=r"(ok) : "r"(bar), "r"(parity) : "memory");
    return ok;
}
__device__ __forceinline__ void mbar_wait(uint32_t bar, uint32_t parity) {
    asm volatile("{\n.reg .pred p;\nW_%=:\nmbarrier.try_wait.parity.shared::cta.b64 p, [%0], %1;\n@!p pmevent 0;\n@!p bra.uni W_%=;\n}\n"
                 ::"r"(bar), "r"(parity) : "memory");
}
__device__ __forceinline__ void st_async(uint32_t addr, uint32_t v, uint32_t bar) {
    asm volatile("st.async.shared::cluster.mbarrier::complete_tx::bytes.b32 [%0], %1, [%2];" ::"r"(addr), "r"(v), "r"(bar) : "memory");
}
__device__ __forceinline__ void st_async_if(bool on, uint32_t addr, uint32_t v, uint32_t bar) {
    asm volatile("{\n.reg .pred p;\nsetp.ne.u32 p, %3, 0;\n@p st.async.shared::cluster.mbarrier::complete_tx::bytes.b32 [%0], %1, [%2];\n}"
                 ::"r"(addr), "r"(v), "r"(bar), "r"((uint32_t)on) : "memory");
}
__device__ __forceinline__ void tma2d(uint32_t dst, const CUtensorMap* tm, int x, int y, uint32_t bar, uint64_t pol) {
    asm volatile("cp.async.bulk.tensor.2d.shared::cluster.global.mbarrier::complete_tx::bytes.L2::cache_hint [%0], [%1, {%3, %4}], [%2], %5;"
                 ::"r"(dst), "l"(tm), "r"(bar), "r"(x), "r"(y), "l"(pol) : "memory");
}
__device__ __forceinline__ bool elect_one() {
    uint32_t e;
    asm volatile("{\n.reg .pred p;\nelect.sync _|p, 0xffffffff;\nselp.u32 %0, 1, 0, p;\n}" : "=r"(e));
    return e;
}
__device__ __forceinline__ void ldsm4(uint32_t& r0, uint32_t& r1, uint32_t& r2, uint32_t& r3, uint32_t a) {
    asm volatile("ldmatrix.sync.aligned.m8n8.x4.shared.b16 {%0,%1,%2,%3}, [%4];" : "=r"(r0), "=r"(r1), "=r"(r2), "=r"(r3) : "r"(a));
}
__device__ __forceinline__ void ldsm4t(uint32_t& r0, uint32_t& r1, uint32_t& r2, uint32_t& r3, uint32_t a) {
    asm volatile("ldmatrix.sync.aligned.m8n8.x4.trans.shared.b16 {%0,%1,%2,%3}, [%4];" : "=r"(r0), "=r"(r1), "=r"(r2), "=r"(r3) : "r"(a));
}
__device__ __forceinline__ void mma(float (&c)[4], uint32_t a0, uint32_t a1, uint32_t a2, uint32_t a3, uint32_t b0, uint32_t b1) {
    asm("mma.sync.aligned.m16n8k16.row.col.f32.bf16.bf16.f32 {%0,%1,%2,%3}, {%4,%5,%6,%7}, {%8,%9}, {%0,%1,%2,%3};"
        : "+f"(c[0]), "+f"(c[1]), "+f"(c[2]), "+f"(c[3]) : "r"(a0), "r"(a1), "r"(a2), "r"(a3), "r"(b0), "r"(b1));
}
__device__ __forceinline__ uint4 lds128(uint32_t a) {
    uint4 v; asm volatile("ld.shared.v4.b32 {%0,%1,%2,%3}, [%4];" : "=r"(v.x), "=r"(v.y), "=r"(v.z), "=r"(v.w) : "r"(a)); return v;
}
__device__ __forceinline__ uint4 lds128_if(bool on, uint32_t a) {
    uint4 v;
    asm volatile("{\n.reg .pred p;\nsetp.ne.u32 p, %5, 0;\nmov.b32 %0, 0;\nmov.b32 %1, 0;\nmov.b32 %2, 0;\nmov.b32 %3, 0;\n"
                 "@p ld.shared.v4.b32 {%0,%1,%2,%3}, [%4];\n}" : "=r"(v.x), "=r"(v.y), "=r"(v.z), "=r"(v.w) : "r"(a), "r"((uint32_t)on));
    return v;
}
__device__ __forceinline__ uint2 lds64_if(bool on, uint32_t a) {
    uint2 v;
    asm volatile("{\n.reg .pred p;\nsetp.ne.u32 p, %3, 0;\nmov.b32 %0, 0;\nmov.b32 %1, 0;\n"
                 "@p ld.shared.v2.b32 {%0,%1}, [%2];\n}" : "=r"(v.x), "=r"(v.y) : "r"(a), "r"((uint32_t)on));
    return v;
}
__device__ __forceinline__ float4 lds128f(uint32_t a) {
    float4 v; asm volatile("ld.shared.v4.f32 {%0,%1,%2,%3}, [%4];" : "=f"(v.x), "=f"(v.y), "=f"(v.z), "=f"(v.w) : "r"(a)); return v;
}
__device__ __forceinline__ float2 lds64f(uint32_t a) {
    float2 v; asm volatile("ld.shared.v2.f32 {%0,%1}, [%2];" : "=f"(v.x), "=f"(v.y) : "r"(a)); return v;
}
__device__ __forceinline__ float lds32f(uint32_t a) { float v; asm volatile("ld.shared.f32 %0, [%1];" : "=f"(v) : "r"(a)); return v; }
__device__ __forceinline__ void cluster_wait() { asm volatile("barrier.cluster.wait.aligned;" ::: "memory"); }
__device__ __forceinline__ void sts32(uint32_t a, uint32_t v) { asm volatile("st.shared.b32 [%0], %1;" ::"r"(a), "r"(v) : "memory"); }
__device__ __forceinline__ uint32_t pack2(float lo, float hi) {
    uint32_t d; asm("cvt.rn.bf16x2.f32 %0, %1, %2;" : "=r"(d) : "f"(hi), "f"(lo)); return d;
}
__device__ __forceinline__ float rbf(float x) { return __uint_as_float(pack2(x, 0.f) << 16); }
__device__ __forceinline__ float ex2(float x) { float y; asm("ex2.approx.ftz.f32 %0, %1;" : "=f"(y) : "f"(x)); return y; }
__device__ __forceinline__ float fsqrt(float x) { float y; asm("sqrt.approx.f32 %0, %1;" : "=f"(y) : "f"(x)); return y; }
__device__ __forceinline__ float fdiv(float a, float b) { float y; asm("div.full.f32 %0, %1, %2;" : "=f"(y) : "f"(a), "f"(b)); return y; }
__device__ __forceinline__ float warp_max(float x) {
    int i = __float_as_int(x), m;
    i ^= (i >> 31) & 0x7fffffff;
    asm volatile("redux.sync.max.s32 %0, %1, 0xffffffff;" : "=r"(m) : "r"(i));
    m ^= (m >> 31) & 0x7fffffff;
    return __int_as_float(m);
}
__device__ __forceinline__ float warp_sum(float x) {
#pragma unroll
    for (int o = 16; o; o >>= 1) x += __shfl_xor_sync(0xffffffffu, x, o);
    return x;
}
__device__ __forceinline__ uint4 ld_relaxed(const uint4* p) {
    uint4 v; asm volatile("ld.relaxed.gpu.global.v4.b32 {%0,%1,%2,%3}, [%4];" : "=r"(v.x), "=r"(v.y), "=r"(v.z), "=r"(v.w) : "l"(p) : "memory");
    return v;
}
__device__ __forceinline__ float rcp(float x) { float y; asm("rcp.approx.ftz.f32 %0, %1;" : "=f"(y) : "f"(x)); return y; }
__device__ __forceinline__ float rsq(float x) { float y; asm("rsqrt.approx.ftz.f32 %0, %1;" : "=f"(y) : "f"(x)); return y; }
__device__ __forceinline__ int fresh_lane() { int l; asm volatile("mov.u32 %0, %%laneid;" : "=r"(l)); return l; }
__device__ __forceinline__ uint32_t badd2(uint32_t a, uint32_t b) { uint32_t d; asm("add.rn.bf16x2 %0, %1, %2;" : "=r"(d) : "r"(a), "r"(b)); return d; }
__device__ __forceinline__ uint32_t lds16(uint32_t a) { uint32_t v; asm volatile("ld.shared.u16 %0, [%1];" : "=r"(v) : "r"(a)); return v; }
__device__ __forceinline__ void sign_off(uint32_t sb) { mbar_arrive_if(fresh_lane() == 0, sb + OFF_BAR + BAR_DONE * 8); }

struct Params {
    const __nv_bfloat16* x;
    const __nv_bfloat16* b1;
    const __nv_bfloat16* b2;
    __nv_bfloat16* out;
    uint32_t zero;
};

__device__ __forceinline__ void xch_send(uint32_t (&s)[4], uint4* dst, uint32_t tag) {
#pragma unroll
    for (int i = 0; i < 4; i++) s[i] = (s[i] & ~1u) | tag;
    asm volatile("st.relaxed.gpu.global.v4.b32 [%0], {%1,%2,%3,%4};" ::"l"(dst), "r"(s[0]), "r"(s[1]), "r"(s[2]), "r"(s[3]) : "memory");
}

__device__ __forceinline__ void xch_recv(uint4& v, const uint4* src, uint32_t tag, uint32_t zero) {
    while (__any_sync(0xffffffffu, (((v.x ^ tag) | (v.y ^ tag)) | ((v.z ^ tag) | (v.w ^ tag))) & (1u | zero))) v = ld_relaxed(src);
}
template <bool ROUND>
__device__ __forceinline__ void softmax4(uint32_t (&s)[4], const uint4& v) {
    float t[4] = {__uint_as_float(s[0]) + __uint_as_float(v.x), __uint_as_float(s[1]) + __uint_as_float(v.y),
                  __uint_as_float(s[2]) + __uint_as_float(v.z), __uint_as_float(s[3]) + __uint_as_float(v.w)};
    if (ROUND) {
#pragma unroll
        for (int i = 0; i < 4; i++) t[i] = rbf(rbf(t[i]) * SCALE);
    }
    constexpr float C = ROUND ? LOG2E : SCALE * LOG2E;
    const float m = warp_max(fmaxf(fmaxf(t[0], t[1]), fmaxf(t[2], t[3]))) * C;
#pragma unroll
    for (int i = 0; i < 4; i++) t[i] = ex2(fmaf(t[i], C, -m));
    s[0] = pack2(t[0], t[1]);
    s[1] = pack2(t[2], t[3]);
    s[2] = __float_as_uint(m);
    uint32_t l;
    asm volatile("redux.sync.add.u32 %0, %1, 0xffffffff;" : "=r"(l) : "r"(__float2uint_rn(((t[0] + t[1]) + (t[2] + t[3])) * 16777216.f)));
    s[3] = __float_as_uint(__uint2float_rn(l));
}

__device__ __forceinline__ void publish_ml(const uint32_t (&s)[4], int k, uint32_t sb, uint32_t rsb, int src, int lane) {
    const uint32_t base = (lane & 16) ? sb : rsb, i = lane & 15;
    st_async(base + i * 4 + (i < 2 ? OFF_ML + k * 64 + src * 8 : OFF_SINK), (lane & 1) ? s[3] : s[2], base + OFF_BAR + (k ? BAR_O + 1 : BAR_M) * 8);
}
__device__ __forceinline__ void publish_o(const float (&o)[4][4], int k, uint32_t sb, uint32_t rsb, int src, int lane) {
    const int g = lane >> 2, j = lane & 3;
    const float lo = (j & 2) ? ((j & 1) ? o[3][0] : o[2][0]) : ((j & 1) ? o[1][0] : o[0][0]);
    const float hi = (j & 2) ? ((j & 1) ? o[3][2] : o[2][2]) : ((j & 1) ? o[1][2] : o[0][2]);
    const uint32_t wd = pack2(lo, hi);
    const uint32_t off = OFF_O + k * 1024 + src * 128 + (8 * j + (((g - 2 * j) ^ (src << 2)) & 7)) * 4, bar = OFF_BAR + (BAR_O + k) * 8;
    st_async(rsb + off, wd, rsb + bar);
    st_async(sb + off, wd, sb + bar);
}

__device__ __forceinline__ uint32_t next_slot(uint32_t sl) { return sl == NSLOT - 1 ? 0 : sl + 1; }
template <int N>
__device__ __forceinline__ uint32_t release_slots(uint32_t bars, uint32_t sl, int lane, const uint32_t* frag, uint32_t zero) {
    uint32_t dep = 0;
#pragma unroll
    for (int i = 0; i < 4 * N; i++) dep |= frag[4 * i];
    uint32_t t = sl + lane;
    if (t >= NSLOT) t -= NSLOT;
    mbar_arrive_if(lane < N, bars + (BAR_EMPTY + t) * 8 + (dep & zero));
    return sl + N >= NSLOT ? sl + N - NSLOT : sl + N;
}

#define TQW 0
__device__ __forceinline__ void attention_role(uint32_t sb, uint32_t rsb, int w, int lane0, uint32_t zero) {
    const int c = blockIdx.x, r = c & 1;
    const int mi = lane0 >> 3, i8 = lane0 & 7;
    const uint32_t bars = sb + OFF_BAR;
    uint32_t koff, voff;
    {
        int row = 16 * w + ((mi & 1) ? 8 + ((i8 + 4) & 7) : i8);
        koff = sb + row * 128 + (((mi >> 1) ^ (row & 7)) << 4);
        int gi = (i8 >> 1) + 4 * (mi >> 1);
        row = 16 * w + ((i8 & 1) ? 8 + ((gi + 4) & 7) : gi);
        voff = sb + row * 128 + (((mi & 1) ^ (row & 7)) << 4);
    }
    uint4* const xin = g_xch + c * 512 + w * 32 + lane0;
    const int xo = (c & 2) ? -1024 : 1024;
    uint32_t hold[HOLD * 16];
#pragma unroll
    for (int i = 0; i < HOLD * 16; i++) hold[i] = 0;

    cluster_wait();
    mbar_wait(bars + BAR_Q1 * 8, 0);

    uint32_t ksl = NWI, kpar = 0;
    uint32_t psl = 0;
#pragma unroll 1
    for (int s = -1;; ++s) {
        const int n = s + 1;
        const uint32_t tag1 = ((n >> 1) & 1) ^ 1, tag2 = ((s >> 1) & 1) ^ 1;
        uint32_t sl = ksl, par = kpar, s1[4] = {0, 0, 0, 0};
        if (n < NB) {
            const int lane = fresh_lane(), j = lane & 3;
            uint4 qa = lds128(sb + OFF_Q1 + n * 128 + j * 32), qb = lds128(sb + OFF_Q1 + n * 128 + j * 32 + 16);
#pragma unroll 1
            for (int cp = 0; cp < 4; cp++) {
                uint32_t base[2];
#pragma unroll
                for (int h = 0; h < 2; h++) {
                    mbar_wait(bars + sl * 8, par);
                    base[h] = koff + sl * SLOT;
                    if (++sl == NSLOT) { sl = 0; par ^= 1; }
                }
#pragma unroll
                for (int h = 0; h < 2; h++) {
                    uint32_t a[16];
                    float acc[4] = {0.f, 0.f, 0.f, 0.f}, acd[4] = {0.f, 0.f, 0.f, 0.f};
#pragma unroll
                    for (int ks = 0; ks < 4; ks++) ldsm4(a[4 * ks], a[4 * ks + 1], a[4 * ks + 2], a[4 * ks + 3], base[h] ^ (ks << 5));
                    mma(acc, a[0], a[1], a[2], a[3], qa.x, qa.y);
                    mma(acd, a[4], a[5], a[6], a[7], qa.z, qa.w);
                    mma(acc, a[8], a[9], a[10], a[11], qb.x, qb.y);
                    mma(acd, a[12], a[13], a[14], a[15], qb.z, qb.w);
                    if (j == cp) { s1[2 * h] = __float_as_uint(acc[0] + acd[0]); s1[2 * h + 1] = __float_as_uint(acc[2] + acd[2]); }
                }
            }
            if (n == 0) mbar_wait(bars + BAR_INIT * 8, 0);
            xch_send(s1, xin + (xo + (n & 1) * 128), tag1);
            TS(0, n * 16 + 0);
        }
        uint32_t s2[4], t1 = 0, here = 0;
        uint4 v2;
        if (s >= 0) {
            const int lane = fresh_lane(), j = lane & 3;
            const uint32_t t0 = clk32();
            uint32_t a[(8 - HOLD) * 16], qf[8];
            float rs;
            uint32_t t = psl;
#pragma unroll
            for (int i = 0; i < 8 - HOLD; i++) {
#pragma unroll
                for (int ks = 0; ks < 4; ks++) {
                    const int q = i * 16 + ks * 4;
                    ldsm4(a[q], a[q + 1], a[q + 2], a[q + 3], (koff + t * SLOT) ^ (ks << 5));
                }
                t = next_slot(t);
            }
            psl = release_slots<8 - HOLD>(bars, psl, lane, a, zero);
            const uint32_t qa = sb + OFF_Q + lane * 8;
            const float2 cs = lds64f(qa + (OFF_CSQ - OFF_Q));
            while (clk32() - t0 < XCH1_DELAY && !mbar_test(bars + BAR_Q * 8, s & 1)) {}
            uint4 v1 = ld_relaxed(xin + (n & 1) * 128);
            mbar_wait(bars + BAR_Q * 8, s & 1);
            TS(0, s * 16 + 4); TQ(s == 7, 1);
            {
                const float4 su = lds128f(sb + OFF_Q + 544);
                const float2 pq = lds64f(qa), pr = lds64f(qa + 256);
                mbar_expect_if(w + lane == 0, bars + BAR_Q * 8, TX_Q);
                const float mean = ((su.x + su.y) + (su.z + su.w)) * (1.f / DM);
                const uint32_t pk = pack2(pq.x + pr.x - mean * cs.x, pq.y + pr.y - mean * cs.y);
#pragma unroll
                for (int i = 0; i < 8; i++) qf[i] = i ? __shfl_xor_sync(0xffffffffu, pk, 4 * i) : pk;
                const uint32_t va = sb + OFF_Q + 512 + (qf[3] & zero);
                const float4 sa = lds128f(va), sc = lds128f(va + 16);
                rs = rsq(fmaxf((((sa.x + sa.y) + (sa.z + sa.w)) + ((sc.x + sc.y) + (sc.z + sc.w))) * (1.f / DM) - mean * mean, 0.f) + LN_EPS);
            }
#pragma unroll
            for (int ch = 0; ch < 8; ch++) {
                const int qx = ch >> 1;
                const uint32_t* kf = ch < HOLD ? hold + ch * 16 : a + (ch - HOLD) * 16;
                float acc[4] = {0.f, 0.f, 0.f, 0.f};
#pragma unroll
                for (int i = 0; i < 4; i++) {
                    const int ks = i ^ qx;
                    mma(acc, kf[4 * ks], kf[4 * ks + 1], kf[4 * ks + 2], kf[4 * ks + 3], qf[2 * i], qf[2 * i + 1]);
                }
                if (ch < 2 || j == qx) { s2[(ch & 1) * 2] = __float_as_uint(acc[0]); s2[(ch & 1) * 2 + 1] = __float_as_uint(acc[2]); }
            }
#pragma unroll
            for (int i = 0; i < 4; i++) s2[i] = __float_as_uint(__uint_as_float(s2[i]) * rs);
            xch_send(s2, xin + (xo + (2 + (s & 1)) * 128), tag2);
            TS(0, s * 16 + 5); TQ(s == 7, 2);
            t1 = clk32();
            t = psl;
#pragma unroll
            for (int i = 0; i < HOLD; i++) {
                const uint32_t base = voff + t * SLOT;
#pragma unroll
                for (int mt = 0; mt < 4; mt++) {
                    const int q = i * 16 + mt * 4;
                    ldsm4t(hold[q], hold[q + 1], hold[q + 2], hold[q + 3], base ^ (mt << 5));
                }
                t = next_slot(t);
                if (i == XCH_AT) {
                    if (n < NB) {
                        release_slots<2>(bars, psl, lane, hold, zero);
                        asm volatile("{\n.reg .pred p, q;\nsetp.lt.u32 p, %3, 8;\nsetp.ne.u32 q, 0, 0;\n"
                                     "@p mbarrier.test_wait.parity.shared::cta.b64 q, [%1], %2;\nselp.u32 %0, 1, 0, q;\n}"
                                     : "=r"(here) : "r"(bars + (sl + lane >= NSLOT ? sl + lane - NSLOT : sl + lane) * 8),
                                       "r"(sl + lane >= NSLOT ? par ^ 1 : par), "r"(lane) : "memory");
                        xch_recv(v1, xin + (n & 1) * 128, tag1, zero);
                        softmax4<true>(s1, v1);
                    }
                    while (clk32() - t1 < XCH2_DELAY) {}
                    v2 = ld_relaxed(xin + (2 + (s & 1)) * 128);
                }
            }
            TS(0, s * 16 + 6);
        } else {
            __nanosleep(600);
            uint4 v1 = ld_relaxed(xin);
            xch_recv(v1, xin, tag1, zero);
            softmax4<true>(s1, v1);
            s2[0] = s2[1] = s2[2] = s2[3] = 0;
            v2 = make_uint4(0, 0, 0, 0);
        }
        float o[4][4];
        if (n < NB) {
            const int lane = fresh_lane(), j4 = (lane & 3) * 4;
            const uint32_t got = __ballot_sync(0xffffffffu, here);
            uint32_t f[2][16], pb[2][2];
            publish_ml(s1, 0, sb, rsb, 4 * r + w, lane);
#pragma unroll
            for (int mt = 0; mt < 4; mt++) o[mt][0] = o[mt][1] = o[mt][2] = o[mt][3] = 0.f;
#pragma unroll
            for (int u = 0; u <= 8; u++) {
                if (u < 8) {
                    const uint32_t base = voff + sl * SLOT;
                    pb[u & 1][0] = __shfl_sync(0xffffffffu, s1[u & 1], j4 + (u >> 1));
                    pb[u & 1][1] = __shfl_sync(0xffffffffu, s1[u & 1], j4 + 16 + (u >> 1));
                    if (!((got >> u) & 1)) mbar_wait(bars + sl * 8, par);
#pragma unroll
                    for (int mt = 0; mt < 4; mt++) ldsm4t(f[u & 1][4 * mt], f[u & 1][4 * mt + 1], f[u & 1][4 * mt + 2], f[u & 1][4 * mt + 3], base ^ (mt << 5));
                    if (++sl == NSLOT) { sl = 0; par ^= 1; }
                }
                if (u == 0) release_slots<HOLD - 2>(bars, psl + 2, s >= 0 ? lane : 32, hold + 32, zero);
                if (u > 0) {
                    const uint32_t* vf = f[(u - 1) & 1];
#pragma unroll
                    for (int mt = 0; mt < 4; mt++) mma(o[mt], vf[4 * mt], vf[4 * mt + 1], vf[4 * mt + 2], vf[4 * mt + 3], pb[(u - 1) & 1][0], pb[(u - 1) & 1][1]);
                }
            }
            publish_o(o, 0, sb, rsb, 4 * r + w, lane);
            TT(n == 7 || n == 0, n ? 1 : 3);
            TQ(n == 7, 0);
            TS(0, n * 16 + 2);
            const uint32_t t2 = clk32();
            while (clk32() - t2 < POST_DELAY) {}
        }
        if (s >= 0) {
            const int lane = fresh_lane(), j = lane & 3;
            uint32_t a[(8 - HOLD) * 16];
            uint32_t t = psl + HOLD >= NSLOT ? psl + HOLD - NSLOT : psl + HOLD;
#pragma unroll
            for (int i = 0; i < 8 - HOLD; i++) {
#pragma unroll
                for (int mt = 0; mt < 4; mt++) {
                    const int q = i * 16 + mt * 4;
                    ldsm4t(a[q], a[q + 1], a[q + 2], a[q + 3], (voff + t * SLOT) ^ (mt << 5));
                }
                t = next_slot(t);
            }
            uint32_t dep = 0;
#pragma unroll
            for (int i = 0; i < 4 * (8 - HOLD); i++) dep |= a[4 * i];
            const uint32_t back = t + NSLOT - 1 - lane;
            mbar_arrive_if(lane < 8 - HOLD, bars + (BAR_EMPTY + (back >= NSLOT ? back - NSLOT : back)) * 8 + (dep & zero));
            xch_recv(v2, xin + (2 + (s & 1)) * 128, tag2 | (dep & zero), zero);
            TQ(s == 7, 3);
            softmax4<false>(s2, v2);
            publish_ml(s2, 1, sb, rsb, 4 * r + w, lane);
            TS(0, s * 16 + 7);
#pragma unroll
            for (int mt = 0; mt < 4; mt++) o[mt][0] = o[mt][1] = o[mt][2] = o[mt][3] = 0.f;
#pragma unroll
            for (int k = 0; k < 8; k++) {
                const uint32_t b0 = __shfl_sync(0xffffffffu, s2[k & 1], 4 * j + (k >> 1));
                const uint32_t b1 = __shfl_sync(0xffffffffu, s2[k & 1], 4 * j + 16 + (k >> 1));
                const uint32_t* vf = k < HOLD ? hold + k * 16 : a + (k - HOLD) * 16;
#pragma unroll
                for (int mt = 0; mt < 4; mt++) mma(o[mt], vf[4 * mt], vf[4 * mt + 1], vf[4 * mt + 2], vf[4 * mt + 3], b0, b1);
            }
            publish_o(o, 1, sb, rsb, 4 * r + w, lane);
            TS(0, s * 16 + 8); TQ(s == 7, 4);
        }
        if (n == NB) { sign_off(sb); TQ_FLUSH(); break; }
        {
            const int lane = fresh_lane();
            uint32_t t = ksl;
#pragma unroll
            for (int ch = 0; ch < HOLD; ch++) {
                const uint32_t base = koff + t * SLOT;
#pragma unroll
                for (int ks = 0; ks < 4; ks++) {
                    const int q = ch * 16 + ks * 4;
                    ldsm4(hold[q], hold[q + 1], hold[q + 2], hold[q + 3], base ^ (ks << 5));
                }
                t = next_slot(t);
            }
            psl = release_slots<HOLD>(bars, ksl, lane, hold, zero);
            TS(0, n * 16 + 3);
        }
        ksl = sl; kpar = par;
    }
}

#undef TQW
#define TQW 4
__device__ __forceinline__ void chain_bar(uint32_t dep) { asm volatile("bar.sync %0, 256;" ::"r"(1 + dep) : "memory"); }
__device__ __forceinline__ void x_bar() { asm volatile("bar.sync 2, 288;" ::: "memory"); }

template <int OFF>
__device__ __forceinline__ void red_out(bool on, const uint4* p, const float (&v)[3]) {
    asm volatile("{\n.reg .pred p;\nsetp.ne.u32 p, %6, 0;\n@p red.relaxed.gpu.global.add.v4.f32 [%0+%5], {%1,%2,%3,%4};\n}"
                 ::"l"(p), "f"(v[0]), "f"(v[1]), "f"(v[2]), "f"(1.0f), "n"(OFF), "r"((uint32_t)on) : "memory");
}

template <int OFF>
__device__ __forceinline__ float4 ld_sum(const uint4* p) {
    float4 v;
    asm volatile("ld.relaxed.gpu.global.v4.f32 {%0,%1,%2,%3}, [%4+%5];" : "=f"(v.x), "=f"(v.y), "=f"(v.z), "=f"(v.w) : "l"(p), "n"(OFF) : "memory");
    return v;
}
template <int OFF>
__device__ __forceinline__ void ld_sum_if(uint32_t on, const uint4* p, float4& v) {
    asm volatile("{\n.reg .pred p;\nsetp.ne.u32 p, %6, 0;\n@p ld.relaxed.gpu.global.v4.f32 {%0,%1,%2,%3}, [%4+%5];\n}"
                 : "+f"(v.x), "+f"(v.y), "+f"(v.z), "+f"(v.w) : "l"(p), "n"(OFF), "r"((uint32_t)on) : "memory");
}
template <int OFF>
__device__ __forceinline__ void poll_sum(const uint4* p, float4 v, float count, uint32_t& y01, uint32_t& y2x) {
    while (!__all_sync(0xffffffffu, v.w == count)) v = ld_sum<OFF>(p);
    y01 = pack2(v.x, v.y); y2x = pack2(v.z, 0.f);
}
template <int OFF, bool BIAS, bool LOOKED>
__device__ __forceinline__ void poll_residual(const uint4* p, const float4& first, float count, uint32_t xrow, int w, uint32_t t0, uint32_t b01, uint32_t b2x,
                                              int lane, uint32_t (&pin)[3], uint32_t zero) {
    const uint32_t tie = clk32() & zero;
    const uint32_t xa = (xrow + w * 80 + (lane & 1) * 48 + (lane >> 2) * 2) | tie;
    uint32_t x01 = lds16(xa) | (lds16(xa + 16) << 16), x2x = lds16(xa + 32), y01, y2x;
#pragma unroll
    for (int i = 0; i < 3; i++) pin[i] |= tie;
    const uint32_t wait = POLL_DELAY + __shfl_sync(0xffffffffu, (pin[0] | pin[1] | pin[2]) & zero, 0);
    while (clk32() - t0 < wait) {}
    poll_sum<OFF>(p, LOOKED ? first : ld_sum<OFF>(p), count, y01, y2x);
    if (BIAS) { y01 = badd2(y01, b01); y2x = badd2(y2x, b2x); }
    x01 = badd2(x01, y01); x2x = badd2(x2x, y2x);
    asm volatile("{\n.reg .pred p;\n.reg .b16 a, b, c, d;\nsetp.eq.u32 p, %3, 0;\nmov.b32 {a, b}, %1;\nmov.b32 {c, d}, %2;\n"
                 "st.shared.b16 [%0], a;\nst.shared.b16 [%0+16], b;\n@p st.shared.b16 [%0+32], c;\n}"
                 ::"r"(xa), "r"(x01), "r"(x2x), "r"(lane & 1) : "memory");
}

template <int K, int OFF>
__device__ __forceinline__ void stage_wo(const uint32_t (&WO)[40], uint32_t par, const uint4* acc, uint32_t sb, int w,
                                         float4& first, uint32_t look, uint32_t zero, bool tq) {
    const int lane = fresh_lane(), g = lane >> 2, j = lane & 3;
    const uint32_t ob = sb + OFF_O + K * 1024 + g * 128 + j * 32 + (g & 1) * 16, ml = sb + OFF_ML + K * 64 + j * 16;
    float e0, e1, inv;
    auto factors = [&]() {
        const float4 mm = lds128f(ml);
        float M = fmaxf(mm.x, mm.z);
        M = fmaxf(M, __shfl_xor_sync(0xffffffffu, M, 1));
        M = fmaxf(M, __shfl_xor_sync(0xffffffffu, M, 2));
        e0 = ex2(mm.x - M); e1 = ex2(mm.z - M);
        float L = e0 * mm.y + e1 * mm.w;
        L += __shfl_xor_sync(0xffffffffu, L, 1);
        L += __shfl_xor_sync(0xffffffffu, L, 2);
        inv = rcp(L) * 16777216.f;
    };
    if (K == 0) {
        mbar_wait(sb + OFF_BAR + BAR_M * 8, par);
        factors();
        mbar_expect_if(w + lane == 0, sb + OFF_BAR + BAR_M * 8, TX_M);
        e0 *= inv; e1 *= inv;
    }
    mbar_wait(sb + OFF_BAR + (BAR_O + K) * 8, par);
    TQ(tq, K * 10 + 0);
    const uint4 B0 = lds128(ob), B1 = lds128(ob ^ 16);
    if (K == 1) factors();
    mbar_expect_if(w + lane == 0, sb + OFF_BAR + (BAR_O + K) * 8, K ? TX_O + TX_M : TX_O);
    const uint32_t B[8] = {B0.x, B0.y, B0.z, B0.w, B1.x, B1.y, B1.z, B1.w};
    float t0[4] = {0.f, 0.f, 0.f, 0.f}, t1[4] = {0.f, 0.f, 0.f, 0.f}, t2[4] = {0.f, 0.f, 0.f, 0.f}, t3[4] = {0.f, 0.f, 0.f, 0.f};
#pragma unroll
    for (int s = 0; s < 4; s++) {
        mma(t0, WO[4 * s], WO[4 * s + 1], WO[4 * s + 2], WO[4 * s + 3], B[2 * s], B[2 * s + 1]);
        mma(t1, WO[16 + 4 * s], WO[16 + 4 * s + 1], WO[16 + 4 * s + 2], WO[16 + 4 * s + 3], B[2 * s], B[2 * s + 1]);
        mma((s & 1) ? t3 : t2, WO[32 + 2 * (s & 2)], WO[33 + 2 * (s & 2)], WO[34 + 2 * (s & 2)], WO[35 + 2 * (s & 2)], B[2 * s], B[2 * s + 1]);
    }
    float v[6] = {e0 * t0[0] + e1 * t0[1], e0 * t0[2] + e1 * t0[3], e0 * t1[0] + e1 * t1[1],
                  e0 * t1[2] + e1 * t1[3], e0 * (t2[0] + t3[2]) + e1 * (t2[1] + t3[3]), 0.f};
    if (K == 1) ld_sum_if<HOP>(look | (__float_as_uint(v[LOOK_V]) & zero), acc, first);
    float u[3];
    const bool odd = j & 1;
#pragma unroll
    for (int i = 0; i < 3; i++) u[i] = (odd ? v[3 + i] : v[i]) + __shfl_xor_sync(0xffffffffu, odd ? v[i] : v[3 + i], 1);
#pragma unroll
    for (int i = 0; i < 3; i++) u[i] = (u[i] + __shfl_xor_sync(0xffffffffu, u[i], 2)) * (K == 1 ? inv : 1.f);
    red_out<OFF>(j < 2, acc, u);
}

template <int K, int OFF>
__device__ __forceinline__ void stage_mlp(const uint32_t (&W1)[20], const uint32_t (&W2)[20], float cs1, uint32_t b2x, uint32_t par,
                                          uint32_t xrow, const uint4* acc, uint32_t t0, uint32_t sb, uint32_t rsb, int r, int w,
                                          bool active, bool last, uint32_t zero, uint32_t b01, uint16_t* out, bool tq) {
    const int lane = fresh_lane(), g = lane >> 2, j = lane & 3, ht = w & 3, kh = w >> 2;
    constexpr uint32_t hb = OFF_H + K * H_SZ, bar = OFF_BAR + (BAR_H + K) * 8;
    const uint32_t jsb = (j & 1) ? rsb : sb;
    uint32_t ad[3] = {xrow + (g & 1) * 320 + j * 16 + kh * 192, jsb + hb + (2 * r + kh) * 128 + (8 * ht + g) * 4, jsb + bar};
    poll_residual<OFF - HOP, false, false>(acc, make_float4(0.f, 0.f, 0.f, 0.f), 64.f, xrow, w, t0, 0, 0, lane, ad, zero);
    TS(1, (xrow - sb - OFF_X) / 40 + (K ? 6 : 1));
    TQ(tq, K * 10 + 2);
    if (!active) return;
    x_bar();
    TQ(tq, K * 10 + 3);
    const uint4 B0 = lds128_if(g < 4, ad[0]);
    const uint2 B2 = lds64_if(g < 4, ad[0] + (128 - kh * 184));
    const uint4 B1 = lds128_if(g < 4, ad[0] + 64);
    float a[4] = {0.f, 0.f, 0.f, 0.f}, b[4] = {0.f, 0.f, 0.f, 0.f}, d[4] = {0.f, 0.f, 0.f, 0.f};
    mma(a, W1[0], W1[1], W1[2], W1[3], B0.x, B0.y);
    mma(b, W1[4], W1[5], W1[6], W1[7], B0.z, B0.w);
    mma(d, W1[16], W1[17], W1[18], W1[19], B2.x, B2.y);
    mma(a, W1[8], W1[9], W1[10], W1[11], B1.x, B1.y);
    mma(b, W1[12], W1[13], W1[14], W1[15], B1.z, B1.w);
    st_async_if(j < 2, ad[1], __float_as_uint(((d[0] + d[3]) + (a[0] + a[3])) + (b[0] + b[3])), ad[2]);
    TQ(tq, K * 10 + 4);
    const float b1v = __uint_as_float(b2x & (0xffff0000u | (lane & zero)));
    mbar_wait(sb + bar, par);
    TQ(tq, K * 10 + 5);
    float4 su = lds128f(sb + hb + 544), q0 = lds128f(sb + hb + 512), q1 = lds128f(sb + hb + 528);
    const uint32_t ha = sb + hb + lane * 4;
    const float4 hp = make_float4(lds32f(ha), lds32f(ha + 128), lds32f(ha + 256), lds32f(ha + 384));
    mbar_expect_if(w + lane == 0, sb + bar, TX_H);
    if (K == 1) mbar_arrive_if(last && lane == 0, sb + OFF_BAR + BAR_DONE * 8);
    float mean = ((su.x + su.y) + (su.z + su.w)) * (1.f / DM);
    float var = fmaxf((((q0.x + q0.y) + (q0.z + q0.w)) + ((q1.x + q1.y) + (q1.z + q1.w))) * (1.f / DM) - mean * mean, 0.f);
    float rs = rsq(fmaf(var, 1.f + LN_EPS, LN_EPS * LN_EPS));
    float pre = fmaf(((hp.x + hp.y) + (hp.z + hp.w)) - mean * cs1, rs, b1v);
    float u2 = pre * fmaf(pre * pre, -2.f * LOG2E * 0.7978845608028654f * 0.044715f, -2.f * LOG2E * 0.7978845608028654f);
    float h0 = pre * rcp(1.f + ex2(u2));
    float h1 = __shfl_xor_sync(0xffffffffu, h0, 8), h2 = __shfl_xor_sync(0xffffffffu, h0, 16), h3 = __shfl_xor_sync(0xffffffffu, h0, 24);
    const uint32_t b0 = pack2(h0, h1), b1 = pack2(h2, h3);
    float v[5];
#pragma unroll
    for (int e = 0; e < 5; e++) {
        float t[4] = {0.f, 0.f, 0.f, 0.f};
        mma(t, W2[4 * e], W2[4 * e + 1], W2[4 * e + 2], W2[4 * e + 3], b0, b1);
        v[e] = t[0] + t[3];
    }
    const bool odd = j & 1;
    float u[3] = {odd ? v[3] : v[0], odd ? v[4] : v[1], odd ? 0.f : v[2]};
    if (K == 0 || out == nullptr) {
        red_out<OFF>(j < 2, acc, u);
    } else if (j < 2) {
        float4 o;
        asm volatile("atom.relaxed.gpu.global.add.v4.f32 {%0,%1,%2,%3}, [%4+%9], {%5,%6,%7,%8};"
                     : "=f"(o.x), "=f"(o.y), "=f"(o.z), "=f"(o.w) : "l"(acc), "f"(u[0]), "f"(u[1]), "f"(u[2]), "f"(1.0f), "n"(OFF) : "memory");
        const int col = w * 40 + j * 24 + g;
        const uint32_t xa = xrow + col * 2;
        uint32_t x01 = lds16(xa) | (lds16(xa + 16) << 16), x2x = lds16(xa + 32);
        x01 = badd2(x01, badd2(pack2(o.x + u[0], o.y + u[1]), b01));
        x2x = badd2(x2x, badd2(pack2(o.z + u[2], 0.f), b2x));
        if (o.w == (float)(ACT_PAIRS - 1)) {
            out[col] = (uint16_t)x01;
            out[col + 8] = (uint16_t)(x01 >> 16);
            if (!odd) out[col + 16] = (uint16_t)x2x;
        }
    }
    if (K == 1) __syncwarp();
}

__device__ __forceinline__ void chain_role(const Params& P, uint32_t sb, uint32_t rsb, int w, int lane) {
    const int c = blockIdx.x, r = c & 1, p = c >> 1;
    const int g = lane >> 2, j = lane & 3, mi = lane >> 3, ri = lane & 7;
    const uint32_t bars = sb + OFF_BAR;
    const uint32_t jsb = (j & 1) ? rsb : sb;
    const bool active = p < ACT_PAIRS, odd = j & 1;
    uint32_t WQ[40], WO[40], W1[20], W2[20];

    uint32_t x0[5];
    {
        const uint32_t* xr = reinterpret_cast<const uint32_t*>(P.x + w * DM);
        uint32_t xw[10];
#pragma unroll
        for (int i = 0; i < 10; i++) xw[i] = __ldg(xr + lane + 32 * i);
        float sum = 0.f;
#pragma unroll
        for (int i = 0; i < 10; i++) sum += __uint_as_float(xw[i] << 16) + __uint_as_float(xw[i] & 0xffff0000u);
        const float mean = warp_sum(sum) * (1.f / DM);
        float sq = 0.f;
#pragma unroll
        for (int i = 0; i < 10; i++) {
            float d0 = __uint_as_float(xw[i] << 16) - mean, d1 = __uint_as_float(xw[i] & 0xffff0000u) - mean;
            sq += d0 * d0 + d1 * d1;
        }
        const float mb = rbf(mean), den = rbf(fsqrt(rbf(rbf(warp_sum(sq) * (1.f / DM)) + LN_EPS)));
#pragma unroll
        for (int i = 0; i < 5; i++) {
            uint32_t v = r ? xw[5 + i] : xw[i];
            float d0 = rbf(__uint_as_float(v << 16) - mb), d1 = rbf(__uint_as_float(v & 0xffff0000u) - mb);
            x0[i] = v;
            sts32(sb + OFF_X + w * 640 + (lane + 32 * i) * 4, pack2(fdiv(d0, den), fdiv(d1, den)));
        }
    }
    const int col = 40 * w + 24 * (j & 1) + g;
    uint32_t b01, b2x;
    {
        const uint16_t* pb2 = reinterpret_cast<const uint16_t*>(P.b2) + 320 * r + col;
        b01 = (uint32_t)pb2[0] | ((uint32_t)pb2[8] << 16);
        b2x = (odd ? 0u : (uint32_t)pb2[16]) | (active ? (uint32_t)reinterpret_cast<const uint16_t*>(P.b1)[32 * p + lane] << 16 : 0u);
    }
    cluster_wait();
#pragma unroll 1
    for (int i = 0; i < 2; i++) mbar_wait(bars + i * 8, 0);
#pragma unroll
    for (int t = 0; t < 10; t++) {
        int k = (mi & 1) * 160 + 32 * (t >> 1) + 8 * (ri >> 1) + 2 * (2 * (t & 1) + (mi >> 1)) + (ri & 1);
        ldsm4t(WQ[4 * t], WQ[4 * t + 1], WQ[4 * t + 2], WQ[4 * t + 3], sb + k * 128 + ((w ^ (k & 7)) << 4));
    }
    uint32_t dep = 0;
#pragma unroll
    for (int t = 0; t < 10; t++) dep |= WQ[4 * t];
    TS(1, 200);
    chain_bar(dep & P.zero);
    mbar_arrive_if(w < 4 && lane < 5, bars + (BAR_EMPTY + lane) * 8);
    {
        const uint32_t pb = OFF_BAR + BAR_P * 8, off = OFF_O + (j * 64 + 8 * w + g) * 4;
        float qp[3];
#pragma unroll
        for (int rd = 0; rd < 3; rd++) {
            const uint32_t xb = sb + OFF_X + (4 * rd + (g >> 1)) * 640 + (g & 1) * 320 + j * 16;
            float a[4] = {0.f, 0.f, 0.f, 0.f};
#pragma unroll
            for (int blk = 0; blk < 5; blk++) {
                const uint4 B = rd < 2 ? lds128(xb + blk * 64) : make_uint4(ONES, ONES, ONES, ONES);
                mma(a, WQ[8 * blk], WQ[8 * blk + 1], WQ[8 * blk + 2], WQ[8 * blk + 3], B.x, B.y);
                mma(a, WQ[8 * blk + 4], WQ[8 * blk + 5], WQ[8 * blk + 6], WQ[8 * blk + 7], B.z, B.w);
            }
            qp[rd] = a[0] + a[3];
            st_async_if(rd < 2 || j == 0, rsb + off + rd * 1024, __float_as_uint(qp[rd]), rsb + pb);
        }
        chain_bar(0);
#pragma unroll
        for (int i = 0; i < 5; i++) sts32(sb + OFF_X + w * 640 + (lane + 32 * i) * 4, x0[i]);
        mbar_wait(sb + pb, 0);
#pragma unroll
        for (int rd = 0; rd < 2; rd++) {
            const float q = qp[rd] + lds32f(sb + off + rd * 1024), qn = __shfl_xor_sync(0xffffffffu, q, 4);
            if (!(g & 1)) sts32(sb + OFF_Q1 + (4 * rd + j) * 128 + ((g >> 1) * 8 + w) * 4, pack2(q, qn));
        }
        if (j == 0) sts32(sb + OFF_CSQ + (8 * w + g) * 4, __float_as_uint(qp[2] + lds32f(sb + off + 2048)));
        __syncwarp();
        mbar_arrive_if(lane == 0, bars + BAR_Q1 * 8);
        asm volatile("{\n.reg .pred p;\nsetp.eq.u32 p, %1, 0;\n@p mbarrier.arrive.relaxed.cluster.shared::cluster.b64 _, [%0];\n}"
                     ::"r"(rsb + OFF_BAR + BAR_Q1 * 8), "r"(lane) : "memory");
    }
    TS(1, 201);
#pragma unroll 1
    for (int i = 5; i < 10; i++) mbar_wait(bars + i * 8, 0);
#pragma unroll
    for (int t = 0; t < 10; t++) {
        int cc = 5 * w + (t < 8 ? 2 * (t >> 2) + (mi & 1) : 4);
        int k = 16 * (ri >> 1) + 8 * (ri & 1) + (((t < 8 ? 2 * (t & 3) : 4 * (t - 8) + 2 * (mi & 1)) + (mi >> 1) + (ri & 6)) & 7);
        ldsm4t(WO[4 * t], WO[4 * t + 1], WO[4 * t + 2], WO[4 * t + 3],
               sb + (5 + (cc >> 3)) * SLOT + k * 128 + (((cc & 7) ^ (k & 7)) << 4));
    }
#pragma unroll 1
    for (int i = 10; i < 15; i++) mbar_wait(bars + i * 8, 0);
#pragma unroll
    for (int t = 0; t < 5; t++) {
        int k = (mi & 1) * 160 + 8 * (ri >> 1) + 2 * (mi >> 1) + (ri & 1) +
                (t < 4 ? (w >> 2) * 96 + 32 * (t >> 1) + 4 * (t & 1) : 64 + 4 * (w >> 2));
        ldsm4t(W1[4 * t], W1[4 * t + 1], W1[4 * t + 2], W1[4 * t + 3], sb + (10 + (k >> 6)) * SLOT + (k & 63) * 64 + (w & 3) * 16);
        int cc = 5 * w + t, k2 = 4 * (mi & 1) + (ri >> 1) + 8 * ((2 * (mi >> 1) + (ri & 1)) ^ (t >= 3));
        ldsm4t(W2[4 * t], W2[4 * t + 1], W2[4 * t + 2], W2[4 * t + 3],
               sb + (10 + (cc >> 3)) * SLOT + 4096 + k2 * 128 + (((cc & 7) ^ (k2 & 7)) << 4));
    }
#pragma unroll
    for (int t = 0; t < 10; t++) dep |= WO[4 * t] | (t < 5 ? W1[4 * (t % 5)] : W2[4 * (t % 5)]);
    chain_bar(dep & P.zero);
    TS(1, 202);
    mbar_arrive_if(w < 4 && lane < 10, bars + (BAR_EMPTY + 5 + lane) * 8);
    float cs1;
    {
        float a[4] = {0.f, 0.f, 0.f, 0.f};
#pragma unroll
        for (int t = 0; t < 5; t++) mma(a, W1[4 * t], W1[4 * t + 1], W1[4 * t + 2], W1[4 * t + 3], ONES, ONES);
        const uint32_t hb = OFF_H + H_SZ, bar = OFF_BAR + (BAR_H + 1) * 8;
        st_async_if(j < 2, jsb + hb + (2 * r + (w >> 2)) * 128 + (8 * (w & 3) + g) * 4, __float_as_uint(a[0] + a[3]), jsb + bar);
        mbar_wait(sb + bar, 0);
        const uint32_t ha = sb + hb + lane * 4;
        const float4 hp = make_float4(lds32f(ha), lds32f(ha + 128), lds32f(ha + 256), lds32f(ha + 384));
        mbar_expect_if(w + lane == 0, sb + bar, TX_H);
        cs1 = (hp.x + hp.y) + (hp.z + hp.w);
    }
    b01 = __shfl_sync(0xffffffffu, b01, lane);
    b2x = __shfl_sync(0xffffffffu, b2x, lane);
    const uint4* acc = acc_ptr(r * 128 + w * 16 + 2 * g + (j & 1));
    uint32_t xrow = sb + OFF_X;

#pragma unroll 1
    for (int s = 0; s <= NB; ++s, acc += HOP / 4, xrow += 640) {
        uint32_t t0 = 0;
        float4 first = make_float4(0.f, 0.f, 0.f, 0.f);
        if (s < NB) {
            stage_wo<0, 0>(WO, s & 1, acc, sb, w, first, 0, 0, s == 7);
            TQ(s == 7, 1);
            t0 = clk32();
            TS(1, s * 16 + 0);
            stage_mlp<0, HOP>(W1, W2, cs1, b2x, s & 1, xrow, acc, t0, sb, rsb, r, w, active, false, P.zero, 0, nullptr, s == 7);
            TQ(s == 7, 6);
            t0 = clk32();
            TS(1, s * 16 + 2);
        }
        if (s >= 1) {
            stage_wo<1, -2 * HOP>(WO, (s - 1) & 1, acc, sb, w, first, s < NB, P.zero, s == 8);
            TQ(s == 8, 11); TQ(s == 7, 20);
            if (s == NB) t0 = clk32();
            TS(1, (s - 1) * 16 + 5);
        }
        if (s < NB) {
            const int ln = fresh_lane();
            const uint32_t qsb = (ln & 1) ? rsb : sb;
            uint32_t ad[3] = {xrow + (ln & 4) * 80 + (ln & 3) * 16, qsb + OFF_Q + r * 256 + (8 * w + (ln >> 2)) * 4, qsb + OFF_BAR + BAR_Q * 8};
            poll_residual<HOP, true, true>(acc, first, (float)ACT_PAIRS, xrow, w, t0, b01, b2x, ln, ad, P.zero);
            TS(1, s * 16 + 3); TQ(s == 7, 7);
            x_bar();
            TQ(s == 7, 8);
            float a[4] = {0.f, 0.f, 0.f, 0.f}, b[4] = {0.f, 0.f, 0.f, 0.f}, d[4] = {0.f, 0.f, 0.f, 0.f};
#pragma unroll
            for (int blk = 0; blk < 5; blk++) {
                const uint4 B = lds128_if(ln < 16, ad[0] + blk * 64);
                mma((2 * blk) % 3 == 0 ? a : (2 * blk) % 3 == 1 ? b : d, WQ[8 * blk], WQ[8 * blk + 1], WQ[8 * blk + 2], WQ[8 * blk + 3], B.x, B.y);
                mma((2 * blk + 1) % 3 == 0 ? a : (2 * blk + 1) % 3 == 1 ? b : d, WQ[8 * blk + 4], WQ[8 * blk + 5], WQ[8 * blk + 6], WQ[8 * blk + 7], B.z, B.w);
            }
            st_async_if((ln & 2) == 0, ad[1], __float_as_uint(((b[0] + b[3]) + (d[0] + d[3])) + (a[0] + a[3])), ad[2]);
            TS(1, s * 16 + 4); TQ(s == 7, 9);
        }
        if (s >= 1 && active) {
            stage_mlp<1, -HOP>(W1, W2, cs1, b2x, s & 1, xrow - 640, acc, t0, sb, rsb, r, w, true, s == NB, P.zero, b01,
                               (s == 1 || s == NB) ? reinterpret_cast<uint16_t*>(P.out) + (s - 1) * DM + 320 * r : nullptr, s == 8);
            TT(s == NB, 2);
            TQ(s == 8, 16); TQ(s == 7, 21);
            TS(1, (s - 1) * 16 + 7);
        }
    }
    if (!active) sign_off(sb);
    TQ_FLUSH();
}

__device__ __forceinline__ void moments_role(const Params& P, uint32_t sb, uint32_t rsb) {
    const int c = blockIdx.x, r = c & 1, p = c >> 1;
    const bool active = p < ACT_PAIRS, writer = !active && p < OUT_PAIR + 4;
    constexpr int w = 9; (void)w;
#pragma unroll 1
    for (int i = 0; i < 3 * (NB + 1); i++) {
        const int s = i / 3, ph = i - 3 * s;
        const int lane = fresh_lane(), g = lane >> 2, j = lane & 3;
        if (ph == 2 && writer && s >= 3) {
            const int b = s - 2, vec = (p - OUT_PAIR) * 32 + lane, col = 40 * (vec >> 4) + 24 * (vec & 1) + ((vec >> 1) & 7);
            const uint4* acc = acc_ptr(r * 128 + vec) + b * (HOP / 4);
            const uint16_t* pb = reinterpret_cast<const uint16_t*>(P.b2) + 320 * r + col;
            const uint32_t xa = sb + OFF_X + b * 640 + col * 2;
            uint32_t x01 = lds16(xa) | (lds16(xa + 16) << 16), x2x = lds16(xa + 32), y01, y2x;
            const uint32_t b01 = (uint32_t)pb[0] | ((uint32_t)pb[8] << 16), b2x = pb[(vec & 1) ? 8 : 16];
            poll_sum<2 * HOP>(acc, ld_sum<2 * HOP>(acc), 64.f, y01, y2x);
            x01 = badd2(x01, y01); x2x = badd2(x2x, y2x);
            poll_sum<3 * HOP>(acc, ld_sum<3 * HOP>(acc), (float)ACT_PAIRS, y01, y2x);
            x01 = badd2(x01, badd2(y01, b01)); x2x = badd2(x2x, badd2(y2x, b2x));
            uint16_t* o = reinterpret_cast<uint16_t*>(P.out) + b * DM + 320 * r + col;
            o[0] = (uint16_t)x01;
            o[8] = (uint16_t)(x01 >> 16);
            if (!(vec & 1)) o[16] = (uint16_t)x2x;
            __syncwarp();
            TS(1, b * 16 + 8);
        }
        if (ph == 2 ? (s == 0 || !active) : (s >= NB || (ph == 0 && !active))) continue;
        const uint32_t xb = sb + OFF_X + (g & 1) * 320 + (g & 2) * 96 + j * 16 + (ph == 2 ? s - 1 : s) * 640;
        const uint32_t xc = xb + 128 - (g & 2) * 92;
        const bool diag = g < 4 && j == (g >> 1), side = g == 4 && j < 2;
        const uint32_t dst = (ph == 1 ? OFF_Q : ph == 0 ? OFF_H : OFF_H + H_SZ) + 512 + (diag ? (r * 4 + g) * 4 : 32 + (r * 2 + j) * 4);
        const uint32_t bar = OFF_BAR + (ph == 1 ? BAR_Q : ph == 0 ? BAR_H : BAR_H + 1) * 8;
        asm volatile("bar.sync %0, 288;" ::"r"(2 + ((xb | xc | dst) & P.zero)) : "memory");
        const uint4 B0 = lds128_if(g < 4, xb);
        const uint4 B1 = lds128_if(g < 4, xb + 64);
        const uint2 B2 = lds64_if(g < 4, xc);
        float a[4] = {0.f, 0.f, 0.f, 0.f}, b[4] = {0.f, 0.f, 0.f, 0.f}, d[4] = {0.f, 0.f, 0.f, 0.f};
        mma(a, B0.x, ONES, B0.y, ONES, B0.x, B0.y);
        mma(b, B0.z, ONES, B0.w, ONES, B0.z, B0.w);
        mma(d, B1.x, ONES, B1.y, ONES, B1.x, B1.y);
        mma(a, B1.z, ONES, B1.w, ONES, B1.z, B1.w);
        mma(b, B2.x, ONES, B2.y, ONES, B2.x, B2.y);
        const float vd = diag ? ((g & 1) ? d[1] : d[0]) : d[2] + d[3], va = diag ? ((g & 1) ? a[1] : a[0]) : a[2] + a[3];
        const float vb = diag ? ((g & 1) ? b[1] : b[0]) : b[2] + b[3];
        if (diag || side) {
            st_async(rsb + dst, __float_as_uint((vd + va) + vb), rsb + bar);
            st_async(sb + dst, __float_as_uint((vd + va) + vb), sb + bar);
        }
        __syncwarp();
        TQ(i == 21, 0); TQ(i == 22, 1); TQ(i == 26, 2);
    }
    TQ_FLUSH();
}

struct Maps { CUtensorMap wq, wo, w1, w2, k, v; };

__device__ __forceinline__ void cluster_arrive() {
    asm volatile("fence.mbarrier_init.release.cluster;\nfence.acq_rel.cta;\nbarrier.cluster.arrive.relaxed.aligned;" ::: "memory");
}

__device__ __forceinline__ void weights_role(const Maps& M, uint32_t sb) {
    const int c = blockIdx.x, p = c >> 1;
    uint64_t pol;
    asm("createpolicy.fractional.L2::evict_first.b64 %0, 1.0;" : "=l"(pol));
    int v = 320 * (c & 1);
    cluster_arrive();
    cluster_wait();
#pragma unroll 1
    for (int i = 5; i < NWI; i++) {
        const uint32_t bar = sb + OFF_BAR + i * 8, dst = sb + i * SLOT;
        const int k = i - WW;
        mbar_wait(sb + OFF_BAR + (k < 5 ? k / 3 : k) * 8, 0);
        const int u = i < 10 ? 64 * p : 32 * p;
        if (elect_one()) {
            mbar_expect(bar, SLOT);
            tma2d(dst, i < 10 ? &M.wo : &M.w1, i < 10 ? v : u, i < 10 ? u : v, bar, pol);
            if (i >= 10) tma2d(dst + 4096, &M.w2, v, u, bar, pol);
        }
        v += i == 9 ? -256 : 64;
        TS(2, i);
    }
#pragma unroll 1
    for (int i = NWI - WW; i < NWI; i++) mbar_wait(sb + OFF_BAR + i * 8, 0);
    if (elect_one()) mbar_arrive(sb + OFF_BAR + BAR_WGT * 8);
}

__device__ __forceinline__ void producer_role(const Maps& M, uint32_t sb) {
    const int c = blockIdx.x;
    const uint32_t bars = sb + OFF_BAR;
    uint64_t pol;
    asm("createpolicy.fractional.L2::evict_first.b64 %0, 1.0;" : "=l"(pol));
    const int x = (c & 2) * 32, y0 = (c >> 2) * SK + (SK - WIN) + (c & 1) * 512;
    uint32_t dst = sb + NWI * SLOT, bar = bars + NWI * 8, epar = 1;
    uint32_t wbar = bar, wpar = 0;
    int win = 0;
#pragma unroll 1
    for (int ii = 0; ii < NB * 16; ii++) {
        if (ii == 15) mbar_wait(bars + BAR_WGT * 8, 0);
        mbar_wait(bar + BAR_EMPTY * 8, epar);
        if (elect_one()) mbar_expect(bar, SLOT);
        const CUtensorMap* tm = (ii & 8) ? &M.v : &M.k;
        const int y = y0 + (ii >> 4) * (32 * SK) + (ii & 7) * 64;
        const bool hi = mbar_test(bars + BAR_WIN * 8, 0), lo = mbar_test(bars + BAR_WIN * 8 + 8, 0);
        const int target = WMAX - (hi ? (lo ? 2 : 3) : (lo ? 1 : 0));
        const int waits = target > win ? 0 : target < win ? 2 : 1;
        win += 1 - waits;
        if (waits == 2) {
            mbar_wait(wbar, wpar);
            wbar += 8; if (wbar == bars + NSLOT * 8) { wbar = bars; wpar ^= 1; }
        }
        if (waits) mbar_wait(wbar, wpar);
        if (elect_one()) tma2d(dst, tm, x, y, bar, pol);
        TS(2, ii + NWI);
        TT(ii == 16, 5);
        if (waits) { wbar += 8; if (wbar == bars + NSLOT * 8) { wbar = bars; wpar ^= 1; } }
        bar += 8; dst += SLOT;
        if (bar == bars + NSLOT * 8) { bar = bars; dst = sb; epar ^= 1; }
    }
}

__global__ void __cluster_dims__(2, 1, 1) __launch_bounds__(NTHREADS, 1)
fused_decode_kernel(const __grid_constant__ Maps M, const __grid_constant__ Params P) {
    extern __shared__ __align__(1024) unsigned char smem[];
    const uint32_t sb = (uint32_t)__cvta_generic_to_shared(smem);
    const int lane = threadIdx.x & 31, c = blockIdx.x;
    const int warp = __shfl_sync(0xffffffffu, threadIdx.x >> 5, 0);
    const uint32_t bars = sb + OFF_BAR;
    TT(warp == 15, 0);
    if (warp < 2 && elect_one()) {
        mbar_init(bars + warp * 8, 1);
        asm volatile("fence.mbarrier_init.release.cluster;" ::: "memory");
        mbar_expect(bars + warp * 8, 160 * 128);
        asm volatile("cp.async.bulk.tensor.2d.shared::cluster.global.mbarrier::complete_tx::bytes [%0], [%1, {%3, %4}], [%2];"
                     ::"r"(sb + warp * (160 * 128)), "l"(&M.wq), "r"(bars + warp * 8), "r"(64 * (c >> 1)), "r"(160 * (2 * (c & 1) + warp)) : "memory");
    }
    if (lane == 0 && warp >= 2 && warp < 7) asm volatile("prefetch.tensormap [%0];" ::"l"(&M.wq + (warp - 1)) : "memory");
    uint32_t rsb;
    asm("mapa.shared::cluster.u32 %0, %1, %2;" : "=r"(rsb) : "r"(sb), "r"((c & 1) ^ 1));

    if (warp < 12) {
        if (lane == 0) {
#pragma unroll 1
            for (int b = 5 + warp; b < BAR_O; b += 12) mbar_init(bars + b * 8, b < BAR_EMPTY ? 1 : 4);
            if (warp >= 2 && warp < 5) { mbar_init(bars + warp * 8, 1); mbar_arrive(bars + warp * 8); }
        }
        __syncwarp();
        cluster_arrive();
        asm volatile("setmaxnreg.inc.sync.aligned.u32 %0;" ::"n"(REG_WORK));
        if (warp < 4) attention_role(sb, rsb, warp, lane, P.zero);
        else chain_role(P, sb, rsb, warp - 4, lane);
    } else {
        asm volatile("setmaxnreg.dec.sync.aligned.u32 %0;" ::"n"(REG_MISC));
        if (warp == 12) {
            cluster_arrive();
            cluster_wait();
            producer_role(M, sb);
            mbar_arrive_if(lane < 2, bars + (BAR_DONE + lane) * 8);
            if (lane == 0) {
            }
        } else if (warp == 14) {
            cluster_arrive();
            TS(2, 200);
#pragma unroll 1
            for (int i = 0; i < 16; i++) g_xch[c * 512 + i * 32 + lane] = make_uint4(0, 0, 0, 0);
            acc_ptr((c & 3) * 64 + lane)[(c >> 2) * (HOP / 16)] = make_uint4(0, 0, 0, 0);
            acc_ptr((c & 3) * 64 + 32 + lane)[(c >> 2) * (HOP / 16)] = make_uint4(0, 0, 0, 0);
            if (c == 0 && lane == 0) g_progress = 0;
            __syncwarp();
            cluster_wait();
            if (lane == 0) {
                unsigned seen;
                asm volatile("atom.acq_rel.gpu.global.add.u32 %0, [%1], 1;" : "=r"(seen) : "l"(&g_arrive) : "memory");
                TS(2, 201);
                const unsigned target = (seen / NCTA + 1) * NCTA;
                do {
                    __nanosleep(200);
                    asm volatile("ld.acquire.gpu.global.u32 %0, [%1];" : "=r"(seen) : "l"(&g_arrive) : "memory");
                } while ((int)(seen - target) < 0);
                mbar_arrive(bars + BAR_INIT * 8);
                TS(2, 202);
                int mine = 0, told = 0, code = LESS0 ^ (LESS0 >> 1);
                uint32_t fb = bars + NWI * 8, fp = 0;
                do {
                    while (mine < NB * 16 && mbar_test(fb, fp)) {
                        mine++;
                        fb += 8; if (fb == bars + NSLOT * 8) { fb = bars; fp ^= 1; }
                    }
                    int all;
                    asm volatile("atom.relaxed.gpu.global.add.u32 %0, [%1], %2;" : "=r"(all) : "l"(&g_progress), "r"(mine - told) : "memory");
                    const int lag = all - mine * NCTA + LEAD_BIAS;
                    const int less = WMAX - min(max(WINDOW + (lag + 256 * LEAD_STEP) / LEAD_STEP - 256, WMAX - 3), WMAX);
                    const int flip = told >= WSHRINK ? code ^ less ^ (less >> 1) : 0;
                    if (flip & 2) mbar_arrive(bars + BAR_WIN * 8);
                    if (flip & 1) mbar_arrive(bars + BAR_WIN * 8 + 8);
                    code ^= flip;
                    told = mine;
                    __nanosleep(PACE_GAP);
                } while (!mbar_test(bars + BAR_END * 8, 0));
                mbar_arrive(bars + BAR_DONE * 8);
            }
        } else if (warp == 15) {
            if (lane == 0) {
#pragma unroll
                for (int b = BAR_O; b <= BAR_WIN + 1; b++) mbar_init(bars + b * 8, b == BAR_Q1 ? 16 : b == BAR_DONE ? 15 : 1);
#pragma unroll
                for (int b = BAR_O; b <= BAR_P; b++)
                    mbar_expect(bars + b * 8, b == BAR_O ? TX_O : b == BAR_O + 1 ? TX_O + TX_M : b == BAR_M ? TX_M : b == BAR_H ? TX_H
                                              : b == BAR_H + 1 ? 512u : b == BAR_Q ? TX_Q : TX_P);
                if ((LESS0 ^ (LESS0 >> 1)) & 2) mbar_arrive(bars + BAR_WIN * 8);
                if ((LESS0 ^ (LESS0 >> 1)) & 1) mbar_arrive(bars + BAR_WIN * 8 + 8);
                if (sb & 1023) __trap();
            }
            __syncwarp();
            cluster_arrive();
            cluster_wait();
            const long long t0 = clock64();
            uint32_t done;
            do {
                __nanosleep(250);
                done = mbar_test(bars + BAR_DONE * 8, 0);
                if (clock64() - t0 > WATCHDOG) __trap();
            } while (!done);
        } else {
            weights_role(M, sb);
            moments_role(P, sb, rsb);
            sign_off(sb);
        }
    }
}

typedef CUresult (*EncodeFn)(CUtensorMap*, CUtensorMapDataType, cuuint32_t, void*, const cuuint64_t*, const cuuint64_t*,
                             const cuuint32_t*, const cuuint32_t*, CUtensorMapInterleave, CUtensorMapSwizzle,
                             CUtensorMapL2promotion, CUtensorMapFloatOOBfill);

bool make_map(EncodeFn enc, CUtensorMap* m, const void* base, uint64_t cols, uint64_t rows, uint32_t bx, uint32_t by, bool swz) {
    cuuint64_t gd[2] = {cols, rows}, gs[1] = {cols * 2};
    cuuint32_t box[2] = {bx, by}, es[2] = {1, 1};
    return enc(m, CU_TENSOR_MAP_DATA_TYPE_BFLOAT16, 2, const_cast<void*>(base), gd, gs, box, es, CU_TENSOR_MAP_INTERLEAVE_NONE,
               swz ? CU_TENSOR_MAP_SWIZZLE_128B : CU_TENSOR_MAP_SWIZZLE_NONE, CU_TENSOR_MAP_L2_PROMOTION_L2_128B,
               CU_TENSOR_MAP_FLOAT_OOB_FILL_NONE) == CUDA_SUCCESS;
}

}

extern "C" void kernel_launch(void* const* d_in, const int* in_sizes, int n_in, void* d_out, int out_size) {
    (void)in_sizes; (void)n_in; (void)out_size;
    void* fn = nullptr;
    cudaDriverEntryPointQueryResult qr;
    if (cudaGetDriverEntryPoint("cuTensorMapEncodeTiled", &fn, cudaEnableDefault, &qr) != cudaSuccess || !fn) return;
    EncodeFn enc = (EncodeFn)fn;
    Maps M;
    bool ok = make_map(enc, &M.k, d_in[1], 128, (uint64_t)NB * 32 * SK, 64, 64, true) &&
              make_map(enc, &M.v, d_in[2], 128, (uint64_t)NB * 32 * SK, 64, 64, true) &&
              make_map(enc, &M.wq, d_in[3], 4096, DM, 64, 160, true) &&
              make_map(enc, &M.wo, d_in[4], DM, 4096, 64, 64, true) &&
              make_map(enc, &M.w1, d_in[6], FF, DM, 32, 64, false) &&
              make_map(enc, &M.w2, d_in[8], DM, FF, 64, 32, true);
    cudaFuncAttributes fa;
    ok = ok && cudaFuncGetAttributes(&fa, fused_decode_kernel) == cudaSuccess &&
         fa.numRegs * 4 >= 3 * REG_WORK + REG_MISC;
    if (!ok) return;
    cudaFuncSetAttribute(fused_decode_kernel, cudaFuncAttributeMaxDynamicSharedMemorySize, SMEM_BYTES);
    Params P;
    P.x = (const __nv_bfloat16*)d_in[0];
    P.b1 = (const __nv_bfloat16*)d_in[7];
    P.b2 = (const __nv_bfloat16*)d_in[9];
    P.out = (__nv_bfloat16*)d_out;
    P.zero = 0;
    fused_decode_kernel<<<NCTA, NTHREADS, SMEM_BYTES>>>(M, P);
}
```
